```python
import torch

def _softmax(x, axis=-1):
    return torch.softmax(x, dim=axis)
def _gelu(x):
    return torch.nn.functional.gelu(x, approximate="tanh")
def _silu(x):
    return torch.nn.functional.silu(x)
def _sigmoid(x):
    return torch.sigmoid(x)
def _layernorm(x, axis=-1, eps=1e-5):
    m = x.mean(dim=axis, keepdim=True)
    v = x.var(dim=axis, keepdim=True, unbiased=False)
    return (x - m) / torch.sqrt(v + eps)
def _scatter_add(tgt, idx, src, axis=0):
    return tgt.clone().index_add_(axis, idx, src)
def _segment_sum(src, seg, n):
    out = torch.zeros((n,) + src.shape[1:], dtype=src.dtype)
    return out.index_add_(0, seg, src)
def _pad(x, pw):
    flat = tuple(v for pair in reversed(pw) for v in pair)
    return torch.nn.functional.pad(x, flat)

kernel_name = 'standalone__dense_activation_gelu__prompt'

def setup_inputs():

    _w = (lambda a: (lambda t: t.to(torch.bfloat16) if t.is_floating_point() else t)(torch.as_tensor(a)))
    B, S, D, F = 1, 2048, 512, 1376
    return {
        "x": _w((lambda *s: torch.randn(*s, dtype=torch.bfloat16) * 0.05)(B, S, D)),
        "w1": _w((lambda *s: torch.randn(*s, dtype=torch.bfloat16) * 3.2)(D, F) * (D ** -0.5)),
        "b1": _w((lambda *s: torch.randn(*s, dtype=torch.bfloat16) * 3.2)(F) * 0.01),
        "w2": _w((lambda *s: torch.randn(*s, dtype=torch.bfloat16) * 0.05)(F, D) * (F ** -0.5)),
        "b2": _w((lambda *s: torch.randn(*s, dtype=torch.bfloat16) * 0.1)(D) * 0.01),
    }

def reference(x, w1, b1, w2, b2):
    h = torch.einsum("bsd,df->bsf", x, w1) + b1
    h = _gelu(h)
    return torch.einsum("bsf,fd->bsd", h, w2) + b2
```

```cpp
#include <cuda_runtime.h>
#include <cuda_bf16.h>
#include <cuda.h>
#include <stdint.h>

namespace {

constexpr int TOK = 2048, DM = 512, FF = 1376;
constexpr int CH = 176;
constexpr int NSLOT = 14, SLOT = 16384;
constexpr int NTHREADS = 384;
constexpr int SM_BAR = NSLOT * SLOT;
constexpr int SMEM_BYTES = SM_BAR + 512 + 512;
constexpr int HCHUNK = 11 * 4096;

#define PREF_KB 0
#define RED_BF16 1
#define TAIL_ORDER 1
#define J0 10
#define GSCHED 1
#define W2_PREFETCH 0
#define PACE_CYC 0
constexpr int B_FULL = 0, B_EMPTY = 14, B_RED = 28, B_PEER = 30, B_FULL2 = 31, B_HF = 37, B_NUM = 61;

__device__ __align__(1024) uint8_t g_h[16 * 8 * HCHUNK];
__device__ uint32_t g_epoch[128 * 32];

#define PROF(i)
#define PROF1(i)
#define PROFX(i)
#define PROFS(i)

__device__ __forceinline__ uint32_t smem_u32(const void* p) { return (uint32_t)__cvta_generic_to_shared(p); }
__device__ __forceinline__ uint32_t elect_one() {
  uint32_t pred = 0, laneid = 0;
  asm volatile("{\n.reg .b32 %%rx;\n.reg .pred %%px;\nelect.sync %%rx|%%px, %2;\n@%%px mov.s32 %1, 1;\nmov.s32 %0, %%rx;\n}\n"
               : "+r"(laneid), "+r"(pred) : "r"(0xFFFFFFFF));
  return pred;
}
__device__ __forceinline__ void mbar_init(uint32_t bar, uint32_t cnt) {
  asm volatile("mbarrier.init.shared::cta.b64 [%0], %1;" ::"r"(bar), "r"(cnt) : "memory");
}
__device__ __forceinline__ void mbar_expect_tx(uint32_t bar, uint32_t bytes) {
  asm volatile("mbarrier.arrive.expect_tx.shared::cta.b64 _, [%0], %1;" ::"r"(bar), "r"(bytes) : "memory");
}
__device__ __forceinline__ void mbar_arrive(uint32_t bar) {
  asm volatile("mbarrier.arrive.shared::cta.b64 _, [%0];" ::"r"(bar) : "memory");
}
__device__ __forceinline__ void mbar_wait(uint32_t bar, uint32_t parity) {
  asm volatile("{\n.reg .pred p;\nWAIT_%=:\nmbarrier.try_wait.parity.shared::cta.b64 p, [%0], %1;\n@p bra DONE_%=;\nbra WAIT_%=;\nDONE_%=:\n}"
               ::"r"(bar), "r"(parity) : "memory");
}
__device__ __forceinline__ void mbar_wait_cluster(uint32_t bar, uint32_t parity) {
  asm volatile("{\n.reg .pred p;\nWAIT_%=:\nmbarrier.try_wait.parity.acquire.cluster.shared::cta.b64 p, [%0], %1;\n@p bra DONE_%=;\nbra WAIT_%=;\nDONE_%=:\n}"
               ::"r"(bar), "r"(parity) : "memory");
}
__device__ __forceinline__ void tma2d(uint32_t dst, const CUtensorMap* m, int c0, int c1, uint32_t bar) {
  asm volatile("cp.async.bulk.tensor.2d.shared::cluster.global.mbarrier::complete_tx::bytes [%0], [%1, {%3, %4}], [%2];"
               ::"r"(dst), "l"(m), "r"(bar), "r"(c0), "r"(c1) : "memory");
}
__device__ __forceinline__ uint32_t mapa(uint32_t addr, uint32_t rank) {
  uint32_t r;
  asm volatile("mapa.shared::cluster.u32 %0, %1, %2;" : "=r"(r) : "r"(addr), "r"(rank));
  return r;
}
__device__ __forceinline__ void wg_fence() { asm volatile("wgmma.fence.sync.aligned;" ::: "memory"); }
__device__ __forceinline__ void wg_commit() { asm volatile("wgmma.commit_group.sync.aligned;" ::: "memory"); }
template <int N> __device__ __forceinline__ void wg_wait() { asm volatile("wgmma.wait_group.sync.aligned %0;" ::"n"(N) : "memory"); }
template <int N> __device__ __forceinline__ void fence_regs(float (&d)[N]) {
#pragma unroll
  for (int i = 0; i < N; i++) asm volatile("" : "+f"(d[i])::"memory");
}
constexpr uint32_t DHI_SW128 = (1024 >> 4) | (1u << 30);
constexpr uint32_t DHI_NONE = (256 >> 4);
__device__ __forceinline__ uint64_t mkdesc(uint32_t lo, uint32_t hi) { return ((uint64_t)hi << 32) | lo; }

__device__ __forceinline__ void wgmma_ss_n112(float (&d)[56], uint64_t da, uint64_t db, int scale_d) {
  asm volatile("{\n.reg .pred p;\nsetp.ne.b32 p, %58, 0;\n"
    "wgmma.mma_async.sync.aligned.m64n112k16.f32.bf16.bf16 "
    "{%0, %1, %2, %3, %4, %5, %6, %7, %8, %9, %10, %11, %12, %13, %14, %15, %16, %17, %18, %19, %20, %21, %22, %23, %24, %25, %26, %27, %28, %29, %30, %31, %32, %33, %34, %35, %36, %37, %38, %39, %40, %41, %42, %43, %44, %45, %46, %47, %48, %49, %50, %51, %52, %53, %54, %55}, "
    "%56, %57, p, 1, 1, 0, 1;\n}\n"
    : "+f"(d[0]), "+f"(d[1]), "+f"(d[2]), "+f"(d[3]), "+f"(d[4]), "+f"(d[5]), "+f"(d[6]), "+f"(d[7]), "+f"(d[8]), "+f"(d[9]), "+f"(d[10]), "+f"(d[11]), "+f"(d[12]), "+f"(d[13]), "+f"(d[14]), "+f"(d[15]), "+f"(d[16]), "+f"(d[17]), "+f"(d[18]), "+f"(d[19]), "+f"(d[20]), "+f"(d[21]), "+f"(d[22]), "+f"(d[23]), "+f"(d[24]), "+f"(d[25]), "+f"(d[26]), "+f"(d[27]), "+f"(d[28]), "+f"(d[29]), "+f"(d[30]), "+f"(d[31]), "+f"(d[32]), "+f"(d[33]), "+f"(d[34]), "+f"(d[35]), "+f"(d[36]), "+f"(d[37]), "+f"(d[38]), "+f"(d[39]), "+f"(d[40]), "+f"(d[41]), "+f"(d[42]), "+f"(d[43]), "+f"(d[44]), "+f"(d[45]), "+f"(d[46]), "+f"(d[47]), "+f"(d[48]), "+f"(d[49]), "+f"(d[50]), "+f"(d[51]), "+f"(d[52]), "+f"(d[53]), "+f"(d[54]), "+f"(d[55])
    : "l"(da), "l"(db), "r"(scale_d));
}
__device__ __forceinline__ void wgmma_ss_n64(float (&d)[32], uint64_t da, uint64_t db, int scale_d) {
  asm volatile("{\n.reg .pred p;\nsetp.ne.b32 p, %34, 0;\n"
    "wgmma.mma_async.sync.aligned.m64n64k16.f32.bf16.bf16 "
    "{%0, %1, %2, %3, %4, %5, %6, %7, %8, %9, %10, %11, %12, %13, %14, %15, %16, %17, %18, %19, %20, %21, %22, %23, %24, %25, %26, %27, %28, %29, %30, %31}, "
    "%32, %33, p, 1, 1, 0, 1;\n}\n"
    : "+f"(d[0]), "+f"(d[1]), "+f"(d[2]), "+f"(d[3]), "+f"(d[4]), "+f"(d[5]), "+f"(d[6]), "+f"(d[7]), "+f"(d[8]), "+f"(d[9]), "+f"(d[10]), "+f"(d[11]), "+f"(d[12]), "+f"(d[13]), "+f"(d[14]), "+f"(d[15]), "+f"(d[16]), "+f"(d[17]), "+f"(d[18]), "+f"(d[19]), "+f"(d[20]), "+f"(d[21]), "+f"(d[22]), "+f"(d[23]), "+f"(d[24]), "+f"(d[25]), "+f"(d[26]), "+f"(d[27]), "+f"(d[28]), "+f"(d[29]), "+f"(d[30]), "+f"(d[31])
    : "l"(da), "l"(db), "r"(scale_d));
}
__device__ __forceinline__ void wgmma_rs2_n128(float (&d0)[32], float (&d1)[32], const uint32_t (&a)[4], uint64_t db, int scale_d) {
  asm volatile("{\n.reg .pred p;\nsetp.ne.b32 p, %69, 0;\n"
    "wgmma.mma_async.sync.aligned.m64n128k16.f32.bf16.bf16 "
    "{%0, %1, %2, %3, %4, %5, %6, %7, %8, %9, %10, %11, %12, %13, %14, %15, %16, %17, %18, %19, %20, %21, %22, %23, %24, %25, %26, %27, %28, %29, %30, %31, %32, %33, %34, %35, %36, %37, %38, %39, %40, %41, %42, %43, %44, %45, %46, %47, %48, %49, %50, %51, %52, %53, %54, %55, %56, %57, %58, %59, %60, %61, %62, %63}, "
    "{%64, %65, %66, %67}, %68, p, 1, 1, 1;\n}\n"
    : "+f"(d0[0]), "+f"(d0[1]), "+f"(d0[2]), "+f"(d0[3]), "+f"(d0[4]), "+f"(d0[5]), "+f"(d0[6]), "+f"(d0[7]), "+f"(d0[8]), "+f"(d0[9]), "+f"(d0[10]), "+f"(d0[11]), "+f"(d0[12]), "+f"(d0[13]), "+f"(d0[14]), "+f"(d0[15]), "+f"(d0[16]), "+f"(d0[17]), "+f"(d0[18]), "+f"(d0[19]), "+f"(d0[20]), "+f"(d0[21]), "+f"(d0[22]), "+f"(d0[23]), "+f"(d0[24]), "+f"(d0[25]), "+f"(d0[26]), "+f"(d0[27]), "+f"(d0[28]), "+f"(d0[29]), "+f"(d0[30]), "+f"(d0[31]), "+f"(d1[0]), "+f"(d1[1]), "+f"(d1[2]), "+f"(d1[3]), "+f"(d1[4]), "+f"(d1[5]), "+f"(d1[6]), "+f"(d1[7]), "+f"(d1[8]), "+f"(d1[9]), "+f"(d1[10]), "+f"(d1[11]), "+f"(d1[12]), "+f"(d1[13]), "+f"(d1[14]), "+f"(d1[15]), "+f"(d1[16]), "+f"(d1[17]), "+f"(d1[18]), "+f"(d1[19]), "+f"(d1[20]), "+f"(d1[21]), "+f"(d1[22]), "+f"(d1[23]), "+f"(d1[24]), "+f"(d1[25]), "+f"(d1[26]), "+f"(d1[27]), "+f"(d1[28]), "+f"(d1[29]), "+f"(d1[30]), "+f"(d1[31])
    : "r"(a[0]), "r"(a[1]), "r"(a[2]), "r"(a[3]), "l"(db), "r"(scale_d));
}
__device__ __forceinline__ void wgmma_ss2_n128(float (&d0)[32], float (&d1)[32], uint64_t da, uint64_t db, int scale_d) {
  asm volatile("{\n.reg .pred p;\nsetp.ne.b32 p, %66, 0;\n"
    "wgmma.mma_async.sync.aligned.m64n128k16.f32.bf16.bf16 "
    "{%0, %1, %2, %3, %4, %5, %6, %7, %8, %9, %10, %11, %12, %13, %14, %15, %16, %17, %18, %19, %20, %21, %22, %23, %24, %25, %26, %27, %28, %29, %30, %31, %32, %33, %34, %35, %36, %37, %38, %39, %40, %41, %42, %43, %44, %45, %46, %47, %48, %49, %50, %51, %52, %53, %54, %55, %56, %57, %58, %59, %60, %61, %62, %63}, "
    "%64, %65, p, 1, 1, 0, 1;\n}\n"
    : "+f"(d0[0]), "+f"(d0[1]), "+f"(d0[2]), "+f"(d0[3]), "+f"(d0[4]), "+f"(d0[5]), "+f"(d0[6]), "+f"(d0[7]), "+f"(d0[8]), "+f"(d0[9]), "+f"(d0[10]), "+f"(d0[11]), "+f"(d0[12]), "+f"(d0[13]), "+f"(d0[14]), "+f"(d0[15]), "+f"(d0[16]), "+f"(d0[17]), "+f"(d0[18]), "+f"(d0[19]), "+f"(d0[20]), "+f"(d0[21]), "+f"(d0[22]), "+f"(d0[23]), "+f"(d0[24]), "+f"(d0[25]), "+f"(d0[26]), "+f"(d0[27]), "+f"(d0[28]), "+f"(d0[29]), "+f"(d0[30]), "+f"(d0[31]), "+f"(d1[0]), "+f"(d1[1]), "+f"(d1[2]), "+f"(d1[3]), "+f"(d1[4]), "+f"(d1[5]), "+f"(d1[6]), "+f"(d1[7]), "+f"(d1[8]), "+f"(d1[9]), "+f"(d1[10]), "+f"(d1[11]), "+f"(d1[12]), "+f"(d1[13]), "+f"(d1[14]), "+f"(d1[15]), "+f"(d1[16]), "+f"(d1[17]), "+f"(d1[18]), "+f"(d1[19]), "+f"(d1[20]), "+f"(d1[21]), "+f"(d1[22]), "+f"(d1[23]), "+f"(d1[24]), "+f"(d1[25]), "+f"(d1[26]), "+f"(d1[27]), "+f"(d1[28]), "+f"(d1[29]), "+f"(d1[30]), "+f"(d1[31])
    : "l"(da), "l"(db), "r"(scale_d));
}

__device__ __forceinline__ float gelu2(float v) {
  const float c0 = 0.7978845608028654f, c1 = 0.7978845608028654f * 0.044715f;
  float u = v * fmaf(c1, v * v, c0);
  float t;
  asm("tanh.approx.f32 %0, %1;" : "=f"(t) : "f"(u));
  return fmaf(v, t, v);
}
__device__ __forceinline__ uint32_t pack_bf16(float lo, float hi) {
  uint32_t r;
  asm("cvt.rn.bf16x2.f32 %0, %1, %2;" : "=r"(r) : "f"(hi), "f"(lo));
  return r;
}
__device__ __forceinline__ float bf_lo(uint32_t v) { return __uint_as_float(v << 16); }
__device__ __forceinline__ float bf_hi(uint32_t v) { return __uint_as_float(v & 0xffff0000u); }
__device__ __forceinline__ void st_frag(uint8_t* p, const uint32_t (&f)[4], uint32_t m0, uint32_t b0, uint32_t m1, uint32_t b1) {
  asm volatile("st.relaxed.gpu.global.v2.u32 [%0], {%1, %2};" ::"l"(p), "r"((f[0] & m0) | b0), "r"(f[2]) : "memory");
  asm volatile("st.relaxed.gpu.global.v2.u32 [%0], {%1, %2};" ::"l"(p + 256), "r"((f[1] & m1) | b1), "r"(f[3]) : "memory");
}
__device__ __forceinline__ uint32_t mbar_try(uint32_t bar, uint32_t parity) {
  uint32_t done;
  asm volatile("{\n.reg .pred p;\nmbarrier.try_wait.parity.shared::cta.b64 p, [%1], %2;\nselp.u32 %0, 1, 0, p;\n}"
               : "=r"(done) : "r"(bar), "r"(parity) : "memory");
  return done;
}
__device__ __forceinline__ void tma5d(uint32_t dst, const CUtensorMap* m, int c0, int c4, uint32_t bar) {
  asm volatile("cp.async.bulk.tensor.5d.shared::cluster.global.mbarrier::complete_tx::bytes [%0], [%1, {%3, %5, %5, %5, %4}], [%2];"
               ::"r"(dst), "l"(m), "r"(bar), "r"(c0), "r"(c4), "r"(0) : "memory");
}

template <int N>
__device__ __forceinline__ void gelu_step(const float (&acc)[N], int s, uint32_t (&frag)[4]) {
  const int j = 2 * s;
  frag[0] = pack_bf16(gelu2(acc[4 * j + 0]), gelu2(acc[4 * j + 1]));
  frag[1] = pack_bf16(gelu2(acc[4 * j + 2]), gelu2(acc[4 * j + 3]));
  frag[2] = pack_bf16(gelu2(acc[4 * j + 4]), gelu2(acc[4 * j + 5]));
  frag[3] = pack_bf16(gelu2(acc[4 * j + 6]), gelu2(acc[4 * j + 7]));
}
__device__ __forceinline__ void bulk_load(uint32_t dst, const void* src, uint32_t bytes, uint32_t bar) {
  asm volatile("cp.async.bulk.shared::cluster.global.mbarrier::complete_tx::bytes [%0], [%1], %2, [%3];"
               ::"r"(dst), "l"(src), "r"(bytes), "r"(bar) : "memory");
}

#define STORE_SCHED_1B(kb) do { \
    if ((kb) == 0) st_frag(gh + 0 * 4096, hA[0], tag); \
    if ((kb) == 2) st_frag(gh + 1 * 4096, hA[1], tag); \
    if ((kb) == 3) st_frag(gh + 2 * 4096, hA[2], tag); \
    if ((kb) == 4) st_frag(gh + 3 * 4096, hA[3], tag); \
    if ((kb) == 6) st_frag(gh + 4 * 4096, hA[4], tag); \
    if ((kb) == 7) st_frag(gh + 5 * 4096, hA[5], tag); } while (0)
#define HPROFCNT()
struct Params {
  const __nv_bfloat16* b1;
  const __nv_bfloat16* b2;
  __nv_bfloat16* out;
  uint8_t* h;
  uint32_t* epoch;
  const uint8_t* x;
  const uint8_t* w1;
  const uint8_t* w2;
};

template <int MODE>
__global__ void __launch_bounds__(NTHREADS, 1)
mlp_fused_kernel(const Params prm, const __grid_constant__ CUtensorMap mapX, const __grid_constant__ CUtensorMap mapW1A,
                 const __grid_constant__ CUtensorMap mapW1B, const __grid_constant__ CUtensorMap mapW2A,
                 const __grid_constant__ CUtensorMap mapW2B, const __grid_constant__ CUtensorMap mapW2P) {
  extern __shared__ __align__(1024) uint8_t smem[];
  const uint32_t sbase = smem_u32(smem);
  const uint32_t bars = sbase + SM_BAR;
  const int warp = __shfl_sync(0xffffffff, threadIdx.x >> 5, 0);
  const int lane = threadIdx.x & 31;
  const int c = blockIdx.x >> 1;
  const int r = blockIdx.x & 1;
  int m, p;
  if (MODE == 1) {
    const int d = c - 36;
    const int p7 = (d * 37) >> 8;
    m = c < 4 ? 15 : (c < 36 ? ((c - 4) & 7) : 8 + d - p7 * 7);
    p = c < 4 ? c : (c < 36 ? ((c - 4) >> 3) : p7);
  } else {
    m = (c & 7) + ((c >> 5) << 3); p = (c >> 3) & 3;
  }
  const int f = 2 * p + r;
  const int c0 = f * CH;
#define FULL(s) (bars + 8 * (B_FULL + (s)))
#define EMPTY(s) (bars + 8 * (B_EMPTY + (s)))
#define SLOTA(s) (sbase + (s) * SLOT)
#define ACQ(s, u, bytes) do { if ((u) > 0) mbar_wait(EMPTY(s), ((u) - 1) & 1); mbar_expect_tx(FULL(s), bytes); } while (0)
#define LDX(kb) do { ACQ(kb, 0, 16384); tma2d(SLOTA(kb), &mapX, (kb) * 64, m * 128, FULL(kb)); } while (0)
#define LDA(kb, s, u) do { ACQ(s, u, 16384); tma2d(SLOTA(s), &mapW1A, c0, (kb) * 64, FULL(s)); \
                           tma2d(SLOTA(s) + 8192, &mapW1A, c0 + 64, (kb) * 64, FULL(s)); } while (0)

#define FULL2(j) (bars + 8 * (B_FULL2 + (j) % 6))
  if (__builtin_expect(warp >= 8, 1)) {
    asm volatile("setmaxnreg.dec.sync.aligned.u32 56;");
    if (warp == 8) {
    if (elect_one()) {
#pragma unroll
      for (int i = 0; i < NSLOT; i++) mbar_init(FULL(i), 1);
      asm volatile("fence.mbarrier_init.release.cluster;" ::: "memory");
      PROF1(54);
    }
    __syncwarp();
    asm volatile("bar.arrive 1, 288;" ::: "memory");
    if (elect_one()) {
#define PACE(n) do { if (PACE_CYC > 0) { while ((uint32_t)(clock() - tp) < (uint32_t)((n) * PACE_CYC)) {} } } while (0)
      const uint32_t tp = clock();
      LDX(0); LDA(0, 8, 0);
      PROF1(55);
      PACE(1); LDX(1); LDA(1, 9, 0); PACE(2); LDX(2); LDA(2, 10, 0); PACE(3); LDX(3); LDA(3, 11, 0);
      PACE(4); LDX(4); LDA(4, 12, 0); PACE(5); LDX(5); LDA(5, 13, 0); PACE(6); LDX(6); LDX(7);
      PROF1(40);
      asm volatile("prefetch.tensormap [%0];" ::"l"(&mapW1B) : "memory");
      asm volatile("prefetch.tensormap [%0];" ::"l"(&mapW2A) : "memory");
      asm volatile("prefetch.tensormap [%0];" ::"l"(&mapW2B) : "memory");
      asm volatile("prefetch.tensormap [%0];" ::"l"(&mapW2P) : "memory");
    }
    __syncwarp();
        __syncwarp();
      asm volatile("bar.sync 2, 384;" ::: "memory");
      asm volatile("barrier.cluster.arrive.relaxed.aligned;" ::: "memory");
      if (elect_one()) {
        LDA(6, 8, 1); LDA(7, 9, 1);
#pragma unroll
        for (int i = 0; i < 4; i++) { ACQ(10 + i, 1, 16384); tma2d(SLOTA(10 + i), &mapW1B, c0 + 112, i * 128, FULL(10 + i)); }
        PROF1(41);
        const int nk = 128 * p + 64 * (1 - r), ns = 128 * p + 64 * r;
        const int k0 = (2 * (p > 0 ? 0 : 1) + r) * 11, k1 = (2 * (p > 1 ? 1 : 2) + r) * 11, k2 = (2 * (p > 2 ? 2 : 3) + r) * 11;
#define OWNP(ws, i, step, bar) do { tma2d(SLOTA(ws) + (i) * 2048, &mapW2B, nk, c0 + 16 * (step), bar); \
                                    tma2d(SLOTA(ws) + 8192 + (i) * 2048, &mapW2B, ns, c0 + 16 * (step), bar); } while (0)
#define PIECE(ws, i, blk, bar) do { tma5d(SLOTA(ws) + (i) * 2048, &mapW2P, nk, blk, bar); \
                                    tma5d(SLOTA(ws) + 8192 + (i) * 2048, &mapW2P, ns, blk, bar); } while (0)
#define LDW(j) do { const int ws = 8 + (j) % 6; \
        mbar_wait(EMPTY(ws), (1 + (j) / 6) & 1); mbar_expect_tx(FULL2(j), ((j) <= 5 ? 4096 : 0) + 12288); \
        if ((j) <= 5) OWNP(ws, 0, (j) + 5, FULL2(j)); \
        PIECE(ws, 1, k0 + (j) - 2, FULL2(j)); PIECE(ws, 2, k1 + (j) - 2, FULL2(j)); PIECE(ws, 3, k2 + (j) - 2, FULL2(j)); PROF1(88 + (j) - 1); } while (0)
        const uint8_t* hsrc = prm.h + (size_t)((m * 2 + r) * 11) * 16384;
#define LDH(s) do { _Pragma("unroll") for (int q = 0; q < 3; q++) { const uint32_t hb = bars + 8 * (B_HF + q * 8 + (s) % 8); \
          mbar_expect_tx(hb, 4096); bulk_load(SLOTA((s) % 8) + q * 4096, hsrc + (s) * 16384 + (q + (q >= p ? 1 : 0)) * 4096, 4096, hb); } \
          PROF1(76 + (s)); } while (0)
        ACQ(8, 2, 16384);
        tma2d(SLOTA(8), &mapW2A, nk, c0, FULL(8)); tma2d(SLOTA(8) + 8192, &mapW2A, ns, c0, FULL(8));
        ACQ(9, 2, 12288);
        OWNP(9, 0, 4, FULL(9)); OWNP(9, 1, 5, FULL(9)); OWNP(9, 2, 6, FULL(9));
        LDW(2);
        LDW(3); PROF1(48); LDH(0);
        LDW(4); LDH(1);
        LDW(5); LDH(2);
        LDW(6); PROF1(49); LDH(3);
        LDW(7); LDH(4);
        LDW(8); LDH(5); LDH(6);
        LDW(9); PROF1(50); LDH(7); LDH(8);
        LDW(10); LDH(9);
        LDW(11); LDH(10);
        LDW(12);
        PROF1(42);
        mbar_expect_tx(bars + 8 * (B_RED + 0), RED_BF16 ? 8192 : 16384);
        mbar_expect_tx(bars + 8 * (B_RED + 1), RED_BF16 ? 8192 : 16384);
      }
      __syncwarp();
      asm volatile("barrier.cluster.wait.aligned;" ::: "memory");
      if (elect_one())
        asm volatile("mbarrier.arrive.release.cluster.shared::cluster.b64 _, [%0];" ::"r"(mapa(bars + 8 * B_PEER, r ^ 1)) : "memory");
    } else {
      const int q = warp - 9;
      const uint32_t tag = (prm.epoch[blockIdx.x * 32] + 1) & 1;
      asm volatile("bar.sync 2, 384;" ::: "memory");
      asm volatile("barrier.cluster.arrive.relaxed.aligned;" ::: "memory");
      const uint8_t* src = prm.h + (size_t)((m * 2 + r) * 11) * 16384 + (q + (q >= p ? 1 : 0)) * 4096;
      const uint32_t dst = sbase + q * 4096;
      const uint32_t chk = dst + lane * 32 + ((lane >> 2) & 3) * 8;
      const uint32_t hf0 = bars + 8 * (B_HF + q * 8);
      uint32_t hpar = 0;
#pragma unroll
      for (int s = 0; s < 11; s++) {
        const uint32_t hf = hf0 + 8 * (s % 8);
        uint32_t spins = 0;
        for (;;) {
          mbar_wait(hf, (hpar >> (s % 8)) & 1);
          hpar ^= 1u << (s % 8);
          uint32_t v0, v1, v2, v3;
          const uint32_t a = chk + (s % 8) * SLOT;
          asm volatile("ld.shared.u32 %0, [%1];" : "=r"(v0) : "r"(a) : "memory");
          asm volatile("ld.shared.u32 %0, [%1];" : "=r"(v1) : "r"(a + 1024) : "memory");
          asm volatile("ld.shared.u32 %0, [%1];" : "=r"(v2) : "r"(a + 2048) : "memory");
          asm volatile("ld.shared.u32 %0, [%1];" : "=r"(v3) : "r"(a + 3072) : "memory");
          const uint32_t all1 = v0 & v1 & v2 & v3, any1 = v0 | v1 | v2 | v3;
          const uint32_t good = (tag ? all1 : ~any1) & 1u;
          if (__builtin_expect(__all_sync(0xffffffff, good), 1)) break;
          HPROFCNT();
          if (++spins > (1u << 16)) __trap();
          if (elect_one()) { mbar_expect_tx(hf, 4096); bulk_load(dst + (s % 8) * SLOT, src + s * 16384, 4096, hf); }
          __syncwarp();
        }
        if (lane == 0) mbar_arrive(FULL2(s + 2));
        if (q == 0 && lane == 0) PROF1(64 + s);
      }
      asm volatile("barrier.cluster.wait.aligned;" ::: "memory");
    }
  } else {
    const int wg = warp >> 2, wq = warp & 3;
    const int t = lane & 3;
    uint32_t bv[22];
    {
      const uint32_t* b1w = reinterpret_cast<const uint32_t*>(prm.b1 + c0) + t;
#pragma unroll
      for (int j = 0; j < 18; j++) bv[j] = __ldg(b1w + 4 * j);
#pragma unroll
      for (int j = 18; j < 22; j++) bv[j] = f < 7 ? __ldg(b1w + 4 * j) : 0u;
    }
    const uint32_t epoch = prm.epoch[blockIdx.x * 32];
    PROFX(120);
    if (warp == 0) {
      if (elect_one()) {
#pragma unroll
        for (int b = B_EMPTY + 8; b < B_NUM; b++) mbar_init(bars + 8 * b, b < B_RED ? 8 : (b >= B_FULL2 && b < B_HF ? 4 : 1));
        asm volatile("fence.mbarrier_init.release.cluster;" ::: "memory");
      }
    }
    __syncwarp();
    PROFX(121);
    asm volatile("bar.arrive 2, 384;" ::: "memory");
    asm volatile("setmaxnreg.inc.sync.aligned.u32 224;");
    PROFX(122);
    asm volatile("bar.sync 1, 288;" ::: "memory");
    asm volatile("barrier.cluster.arrive.relaxed.aligned;" ::: "memory");
    PROFX(123);
    float accA[56], accB[32], accK[32], accS[32];
#pragma unroll
    for (int j = 0; j < 14; j++) { accA[4 * j] = accA[4 * j + 2] = bf_lo(bv[j]); accA[4 * j + 1] = accA[4 * j + 3] = bf_hi(bv[j]); }
#pragma unroll
    for (int j = 0; j < 8; j++) { accB[4 * j] = accB[4 * j + 2] = bf_lo(bv[14 + j]); accB[4 * j + 1] = accB[4 * j + 3] = bf_hi(bv[14 + j]); }
    fence_regs(accA); fence_regs(accB);
    PROF(0);

    const uint32_t dbase = (sbase & 0x3FFFF) >> 4;
    const uint32_t dx = __shfl_sync(0xffffffff, dbase + wg * 512 + (1u << 16), 0);
    const uint32_t dw = __shfl_sync(0xffffffff, dbase, 0);
#define REL(s) do { if (lane == 0) mbar_arrive(EMPTY(s)); } while (0)
#define SCHED_FENCE(i) do { if (epoch == 0xFFFFFF00u + (i)) __trap(); } while (0)
#define DESC_X(kb, kk) mkdesc(dx + (kb) * 1024 + (kk) * 2, DHI_SW128)
#define DESC_W(s, off, lbo) mkdesc(dw + (s) * 1024 + ((off) >> 4) + (((lbo) >> 4) << 16), DHI_SW128)

    {
      int s = 8;
#pragma unroll 1
      for (int kb = 0; kb < 8; kb++) {
        mbar_wait(FULL(kb), 0);
        mbar_wait(FULL(s), kb >= 6);
        if (kb == 0) PROF(1);
        wg_fence();
#pragma unroll
        for (int kk = 0; kk < 4; kk++) wgmma_ss_n112(accA, DESC_X(kb, kk), DESC_W(s, kk * 2048, 8192), 1);
        wg_commit();
        wg_wait<1>();
        if (kb > 0) REL(s == 8 ? 13 : s - 1);
        s = (s == 13) ? 8 : s + 1;
      }
    }
    PROF(2);
    const uint32_t tag = (epoch + 1) & 1;
    uint8_t* gh = prm.h + (size_t)((m * 2 + r) * 11) * 16384 + p * 4096 + wg * 2048 + wq * 512 + (t >> 1) * 128 + (lane >> 2) * 16 + (t & 1) * 8;
    const bool tl = (t == 0 || t == 3);
    const uint32_t m0 = (tl && ((lane >> 2) & 1) == 0) ? ~1u : ~0u, b0 = (m0 != ~0u) ? tag : 0u;
    const uint32_t m1 = (tl && ((lane >> 2) & 1) == 1) ? ~1u : ~0u, b1 = (m1 != ~0u) ? tag : 0u;
    uint32_t hO[11][4];
#define GELU(s) do { if ((s) < 7) gelu_step(accA, (s), hO[s]); else gelu_step(accB, (s) - 7, hO[s]); \
                     st_frag(gh + (s) * 16384, hO[s], m0, b0, m1, b1); } while (0)
    const uint32_t dh = __shfl_sync(0xffffffff, dbase + wg * 128 + (8u << 16), 0);
#define DESC_W2(j, off) mkdesc(dw + (8 + (j) % 6) * 1024 + ((off) >> 4) + ((8192u >> 4) << 16), DHI_SW128)
#define DESC_H(s, q) mkdesc(dh + ((s) % 8) * 1024 + (q) * 256, DHI_NONE)
    uint32_t rdy = 0;
#pragma unroll
    for (int i = 0; i < 4; i++) {
      if (!rdy) mbar_wait(FULL(10 + i), 1);
      wg_fence();
#pragma unroll
      for (int kk = 0; kk < 8; kk++)
        wgmma_ss_n64(accB, DESC_X(2 * i + (kk >> 2), kk & 3), DESC_W(10 + i, kk * 2048, 8192), 1);
      wg_commit();
      wg_wait<1>();
      REL(9 + i);
      if (i == 0) fence_regs(accA);
      SCHED_FENCE(i);
      rdy = i < 3 ? mbar_try(FULL(11 + i), 1) : mbar_try(FULL(8), 0);
      if (i == 0) { GELU(0); GELU(1); }
      if (i == 1) { GELU(2); GELU(3); }
      if (i >= 2) GELU(i + 2);
      PROF(11 + i);
    }
    PROF(3);
    uint32_t b2v[8];
#pragma unroll
    for (int j = 0; j < J0; j++) {
      if (!rdy) { if (j < 2) mbar_wait(FULL(8 + j), 0); else mbar_wait(FULL2(j), j >= 8); }
      PROFS(100 + j);
      wg_fence();
      if (j == 0) {
#pragma unroll
        for (int kk = 0; kk < 4; kk++) wgmma_rs2_n128(accS, accK, hO[kk], DESC_W2(0, kk * 2048), kk != 0);
      } else if (j == 1) {
#pragma unroll
        for (int kk = 0; kk < 3; kk++) wgmma_rs2_n128(accS, accK, hO[4 + kk], DESC_W2(1, kk * 2048), 1);
      } else {
        if (j <= 5) wgmma_rs2_n128(accS, accK, hO[j + 5], DESC_W2(j, 0), 1);
#pragma unroll
        for (int q = 0; q < 3; q++) wgmma_ss2_n128(accS, accK, DESC_H(j - 2, q), DESC_W2(j, (q + 1) * 2048), 1);
      }
      wg_commit();
      wg_wait<1>();
      if (j == 0) { REL(13); fence_regs(accB); }
      else if (j <= 8) REL(8 + (j - 1) % 6);
      SCHED_FENCE(4 + j);
      if (j < J0 - 1) rdy = (j == 0) ? mbar_try(FULL(9), 0) : mbar_try(FULL2(j + 1), (j + 1) >= 8);
      if (j == 0) { GELU(6); GELU(7); }
      if (j >= 1 && j <= 3) GELU(j + 7);
      if (j == 5) asm volatile("barrier.cluster.wait.aligned;" ::: "memory");
      if (j == 6) {
        const uint32_t* b2w = reinterpret_cast<const uint32_t*>(prm.b2 + 128 * p + 64 * r) + t;
#pragma unroll
        for (int jj = 0; jj < 8; jj++) b2v[jj] = __ldg(b2w + 4 * jj);
      }
      if (j == 1) PROF(4); if (j == 3) PROF(5); if (j == 5) PROF(6);
    }
    PROF(7);
    float accK2[32];
#define BAR_IF(w, ins) asm volatile("{\n.reg .pred p;\nsetp.eq.u32 p, %0, " #w ";\n@p " ins "\n}" ::"r"(wg) : "memory")
    if (TAIL_ORDER) BAR_IF(1, "bar.sync 3, 256;");
#pragma unroll
    for (int j = J0; j < 13; j++) {
      mbar_wait(FULL2(j), 1);
      PROFS(100 + j - (j > 11));
      wg_fence();
#pragma unroll
      for (int q = 0; q < 3; q++) wgmma_ss_n64(accS, DESC_H(j - 2, q), DESC_W2(j, (q + 1) * 2048), 1);
      wg_commit();
      if (j == J0) {
        wg_wait<1>();
        if (J0 == 8) REL(9);
        fence_regs(accK);
#pragma unroll
        for (int i = 0; i < 32; i++) asm volatile("mov.b32 %0, %1;" : "=f"(accK2[i]) : "f"(accK[i]));
      }
    }
    if (TAIL_ORDER) {
      BAR_IF(0, "bar.arrive 3, 256;"); BAR_IF(1, "bar.arrive 4, 256;");
      mbar_wait_cluster(bars + 8 * B_PEER, 0);
      wg_wait<0>();
      fence_regs(accS);
    }
    const int tw = threadIdx.x & 127;
    const uint32_t rbuf = SLOTA(3 + wg) + tw * 16;
    if (!TAIL_ORDER) {
      wg_fence();
#pragma unroll
      for (int q = 0; q < 3; q++) wgmma_ss_n64(accK2, DESC_H(J0 - 2, q), DESC_W2(J0, 8192 + (q + 1) * 2048), 1);
      wg_commit();
      mbar_wait_cluster(bars + 8 * B_PEER, 0);
      wg_wait<1>();
      fence_regs(accS);
    }
    PROF(8);
    {
      const uint32_t rdst = mapa(rbuf, r ^ 1);
      const uint32_t rbar = mapa(bars + 8 * (B_RED + wg), r ^ 1);
#pragma unroll
      for (int q = 0; q < 4; q++)
        asm volatile("st.async.weak.shared::cluster.mbarrier::complete_tx::bytes.v4.b32 [%0], {%1, %2, %3, %4}, [%5];"
                     ::"r"(rdst + q * 2048), "r"(pack_bf16(accS[8 * q + 0], accS[8 * q + 1])), "r"(pack_bf16(accS[8 * q + 2], accS[8 * q + 3])),
                       "r"(pack_bf16(accS[8 * q + 4], accS[8 * q + 5])), "r"(pack_bf16(accS[8 * q + 6], accS[8 * q + 7])), "r"(rbar) : "memory");
    }
    if (TAIL_ORDER) {
      BAR_IF(0, "bar.sync 4, 256;");
      BAR_IF(1, "bar.sync 5, 256;");
    }
    wg_fence();
#pragma unroll
    for (int j = TAIL_ORDER ? J0 : J0 + 1; j < 13; j++) {
#pragma unroll
      for (int q = 0; q < 3; q++) wgmma_ss_n64(accK2, DESC_H(j - 2, q), DESC_W2(j, 8192 + (q + 1) * 2048), 1);
    }
    wg_commit();
    if (TAIL_ORDER) BAR_IF(0, "bar.arrive 5, 256;");
    mbar_wait(EMPTY(9), 1);
    wg_wait<0>();
    fence_regs(accK2);
    mbar_wait_cluster(bars + 8 * (B_RED + wg), 0);
    PROF(9);
    uint32_t pk[16];
#pragma unroll
    for (int q = 0; q < 4; q++) {
      uint4 v;
      asm volatile("ld.shared.v4.u32 {%0, %1, %2, %3}, [%4];" : "=r"(v.x), "=r"(v.y), "=r"(v.z), "=r"(v.w) : "r"(rbuf + q * 2048) : "memory");
      const float bl0 = bf_lo(b2v[2 * q]), bh0 = bf_hi(b2v[2 * q]), bl1 = bf_lo(b2v[2 * q + 1]), bh1 = bf_hi(b2v[2 * q + 1]);
      pk[4 * q + 0] = pack_bf16(fmaf(accK2[8 * q + 0] + bf_lo(v.x), 0.5f, bl0), fmaf(accK2[8 * q + 1] + bf_hi(v.x), 0.5f, bh0));
      pk[4 * q + 1] = pack_bf16(fmaf(accK2[8 * q + 2] + bf_lo(v.y), 0.5f, bl0), fmaf(accK2[8 * q + 3] + bf_hi(v.y), 0.5f, bh0));
      pk[4 * q + 2] = pack_bf16(fmaf(accK2[8 * q + 4] + bf_lo(v.z), 0.5f, bl1), fmaf(accK2[8 * q + 5] + bf_hi(v.z), 0.5f, bh1));
      pk[4 * q + 3] = pack_bf16(fmaf(accK2[8 * q + 6] + bf_lo(v.w), 0.5f, bl1), fmaf(accK2[8 * q + 7] + bf_hi(v.w), 0.5f, bh1));
    }
    const uint32_t stg = SLOTA(5) + warp * 2048;
    {
      const int mi = lane >> 3, row = (lane & 7) + 8 * (mi & 1);
#pragma unroll
      for (int q = 0; q < 8; q += 2) {
        const int blk = q + (mi >> 1);
        const uint32_t a = stg + row * 128 + ((blk ^ (row & 7)) << 4);
        asm volatile("stmatrix.sync.aligned.m8n8.x4.shared.b16 [%0], {%1, %2, %3, %4};"
                     ::"r"(a), "r"(pk[2 * q]), "r"(pk[2 * q + 1]), "r"(pk[2 * q + 2]), "r"(pk[2 * q + 3]) : "memory");
      }
    }
    __syncwarp();
    {
      __nv_bfloat16* orow = prm.out + (size_t)(m * 128 + wg * 64 + wq * 16) * DM + 128 * p + 64 * r;
#pragma unroll
      for (int i = 0; i < 4; i++) {
        const int row = i * 4 + (lane >> 3), ch = lane & 7;
        uint4 v;
        asm volatile("ld.shared.v4.u32 {%0, %1, %2, %3}, [%4];" : "=r"(v.x), "=r"(v.y), "=r"(v.z), "=r"(v.w)
                     : "r"(stg + row * 128 + ((ch ^ (row & 7)) << 4)) : "memory");
        *reinterpret_cast<uint4*>(orow + row * DM + ch * 8) = v;
      }
    }
    if (threadIdx.x == 0) prm.epoch[blockIdx.x * 32] = epoch + 1;
    PROF(10);
  }
}

typedef CUresult (*EncodeFn)(CUtensorMap*, CUtensorMapDataType, cuuint32_t, void*, const cuuint64_t*, const cuuint64_t*,
                             const cuuint32_t*, const cuuint32_t*, CUtensorMapInterleave, CUtensorMapSwizzle,
                             CUtensorMapL2promotion, CUtensorMapFloatOOBfill);

void make_map(EncodeFn enc, CUtensorMap* map, const void* ptr, uint64_t cols, uint64_t rows, uint32_t box_cols, uint32_t box_rows) {
  cuuint64_t dims[2] = {cols, rows};
  cuuint64_t strides[1] = {cols * 2};
  cuuint32_t box[2] = {box_cols, box_rows};
  cuuint32_t es[2] = {1, 1};
  enc(map, CU_TENSOR_MAP_DATA_TYPE_BFLOAT16, 2, const_cast<void*>(ptr), dims, strides, box, es, CU_TENSOR_MAP_INTERLEAVE_NONE,
      CU_TENSOR_MAP_SWIZZLE_128B, CU_TENSOR_MAP_L2_PROMOTION_L2_128B, CU_TENSOR_MAP_FLOAT_OOB_FILL_NONE);
}

void make_map_perm(EncodeFn enc, CUtensorMap* map, const void* ptr) {
  cuuint64_t dims[5] = {512, 2, 2, 4, 86};
  cuuint64_t strides[4] = {1024, 8 * 1024, 2 * 1024, 16 * 1024};
  cuuint32_t box[5] = {64, 2, 2, 4, 1};
  cuuint32_t es[5] = {1, 1, 1, 1, 1};
  CUresult rc = enc(map, CU_TENSOR_MAP_DATA_TYPE_BFLOAT16, 5, const_cast<void*>(ptr), dims, strides, box, es, CU_TENSOR_MAP_INTERLEAVE_NONE,
      CU_TENSOR_MAP_SWIZZLE_128B, CU_TENSOR_MAP_L2_PROMOTION_L2_128B, CU_TENSOR_MAP_FLOAT_OOB_FILL_NONE);
  (void)rc;
}

}

extern "C" void kernel_launch(void* const* d_in, const int* in_sizes, int n_in, void* d_out, int out_size) {
  (void)in_sizes; (void)n_in; (void)out_size;
  static EncodeFn enc = nullptr;
  static int mode = 0;
  static uint8_t* scratch = nullptr;
  static uint32_t* counters = nullptr;
  if (!enc) {
    void* fn = nullptr;
    cudaDriverEntryPointQueryResult q;
    cudaGetDriverEntryPoint("cuTensorMapEncodeTiled", &fn, cudaEnableDefault, &q);
    enc = (EncodeFn)fn;
    cudaGetSymbolAddress((void**)&scratch, g_h);
    cudaGetSymbolAddress((void**)&counters, g_epoch);
    cudaFuncSetAttribute(mlp_fused_kernel<0>, cudaFuncAttributeMaxDynamicSharedMemorySize, SMEM_BYTES);
    cudaFuncSetAttribute(mlp_fused_kernel<1>, cudaFuncAttributeMaxDynamicSharedMemorySize, SMEM_BYTES);
    cudaLaunchConfig_t cfg = {};
    cfg.gridDim = dim3(128); cfg.blockDim = dim3(NTHREADS); cfg.dynamicSmemBytes = SMEM_BYTES;
    cudaLaunchAttribute at[1];
    at[0].id = cudaLaunchAttributeClusterDimension;
    at[0].val.clusterDim.x = 8; at[0].val.clusterDim.y = 1; at[0].val.clusterDim.z = 1;
    cfg.attrs = at; cfg.numAttrs = 1;
    int n8 = 0;
    if (cudaOccupancyMaxActiveClusters(&n8, mlp_fused_kernel<1>, &cfg) != cudaSuccess) { n8 = 0; (void)cudaGetLastError(); }
    mode = (n8 == 15) ? 1 : 0;
  }
  CUtensorMap mX, mW1A, mW1B, mW2A, mW2B, mW2P;
  make_map(enc, &mX, d_in[0], DM, TOK, 64, 128);
  make_map(enc, &mW1A, d_in[1], FF, DM, 64, 64);
  make_map(enc, &mW1B, d_in[1], FF, DM, 64, 128);
  make_map(enc, &mW2A, d_in[3], DM, FF, 64, 64);
  make_map(enc, &mW2B, d_in[3], DM, FF, 64, 16);
  make_map_perm(enc, &mW2P, d_in[3]);
  Params prm;
  prm.b1 = (const __nv_bfloat16*)d_in[2];
  prm.b2 = (const __nv_bfloat16*)d_in[4];
  prm.out = (__nv_bfloat16*)d_out;
  prm.h = scratch;
  prm.epoch = counters;
  prm.x = (const uint8_t*)d_in[0];
  prm.w1 = (const uint8_t*)d_in[1];
  prm.w2 = (const uint8_t*)d_in[3];
  cudaLaunchConfig_t cfg = {};
  cfg.gridDim = dim3(128); cfg.blockDim = dim3(NTHREADS); cfg.dynamicSmemBytes = SMEM_BYTES;
  cfg.stream = cudaStreamPerThread;
  cudaLaunchAttribute at[1];
  at[0].id = cudaLaunchAttributeClusterDimension;
  at[0].val.clusterDim.x = 2; at[0].val.clusterDim.y = 1; at[0].val.clusterDim.z = 1;
  cfg.attrs = at; cfg.numAttrs = 1;
  if (mode == 1) cudaLaunchKernelEx(&cfg, mlp_fused_kernel<1>, prm, mX, mW1A, mW1B, mW2A, mW2B, mW2P);
  else cudaLaunchKernelEx(&cfg, mlp_fused_kernel<0>, prm, mX, mW1A, mW1B, mW2A, mW2B, mW2P);
}
```

```cpp
#include <cuda_runtime.h>
#include <cuda_bf16.h>
#include <cuda.h>
#include <stdint.h>

namespace {

constexpr int TOK = 2048, DM = 512, FF = 1376;
constexpr int CH = 176;
constexpr int NSLOT = 14, SLOT = 16384;
constexpr int NTHREADS = 384;
constexpr int SM_BAR = NSLOT * SLOT;
constexpr int SMEM_BYTES = SM_BAR + 512 + 512;
constexpr int HCHUNK = 11 * 4096;

#define W1_48 1
#define FIRST_CPASYNC 1
#define XPROMO CU_TENSOR_MAP_L2_PROMOTION_L2_128B
#define WPROMO CU_TENSOR_MAP_L2_PROMOTION_L2_128B
#define TAIL_ORDER 1
#define H10_GATE 5
#define HGATES 1
#define JW 12
#define CP_FIRST 1
#define J0 10
#define GSCHED 1
#define W2_PREFETCH 1
constexpr int B_FULL = 0, B_EMPTY = 14, B_RED = 28, B_PEER = 30, B_FULL2 = 31, B_HF = 37, B_HR = 45, B_FULL3 = 48, B_NUM = 50;

__device__ __align__(1024) uint8_t g_h[16 * 8 * HCHUNK];
__device__ uint32_t g_epoch[128 * 32];

#define STAMP(i)
#define STAMP1(i)
#define STAMPN(i)
#define STAMPH(i)
#define PROF(i)
#define PROF1(i)
#define PROFX(i)
#define PROFS(i)

__device__ __forceinline__ uint32_t smem_u32(const void* p) { return (uint32_t)__cvta_generic_to_shared(p); }
__device__ __forceinline__ uint32_t elect_one() {
  uint32_t pred = 0, laneid = 0;
  asm volatile("{\n.reg .b32 %%rx;\n.reg .pred %%px;\nelect.sync %%rx|%%px, %2;\n@%%px mov.s32 %1, 1;\nmov.s32 %0, %%rx;\n}\n"
               : "+r"(laneid), "+r"(pred) : "r"(0xFFFFFFFF));
  return pred;
}
__device__ __forceinline__ void mbar_init(uint32_t bar, uint32_t cnt) {
  asm volatile("mbarrier.init.shared::cta.b64 [%0], %1;" ::"r"(bar), "r"(cnt) : "memory");
}
__device__ __forceinline__ void mbar_expect_tx(uint32_t bar, uint32_t bytes) {
  asm volatile("mbarrier.arrive.expect_tx.shared::cta.b64 _, [%0], %1;" ::"r"(bar), "r"(bytes) : "memory");
}
__device__ __forceinline__ void mbar_arrive(uint32_t bar) {
  asm volatile("mbarrier.arrive.shared::cta.b64 _, [%0];" ::"r"(bar) : "memory");
}
__device__ __forceinline__ void mbar_wait(uint32_t bar, uint32_t parity) {
  asm volatile("{\n.reg .pred p;\nWAIT_%=:\nmbarrier.try_wait.parity.shared::cta.b64 p, [%0], %1;\n@p bra DONE_%=;\nbra WAIT_%=;\nDONE_%=:\n}"
               ::"r"(bar), "r"(parity) : "memory");
}
__device__ __forceinline__ void mbar_wait_cluster(uint32_t bar, uint32_t parity) {
  asm volatile("{\n.reg .pred p;\nWAIT_%=:\nmbarrier.try_wait.parity.acquire.cluster.shared::cta.b64 p, [%0], %1;\n@p bra DONE_%=;\nbra WAIT_%=;\nDONE_%=:\n}"
               ::"r"(bar), "r"(parity) : "memory");
}
__device__ __forceinline__ void tma2d(uint32_t dst, const CUtensorMap* m, int c0, int c1, uint32_t bar) {
  asm volatile("cp.async.bulk.tensor.2d.shared::cluster.global.mbarrier::complete_tx::bytes [%0], [%1, {%3, %4}], [%2];"
               ::"r"(dst), "l"(m), "r"(bar), "r"(c0), "r"(c1) : "memory");
}
__device__ __forceinline__ uint32_t mapa(uint32_t addr, uint32_t rank) {
  uint32_t r;
  asm volatile("mapa.shared::cluster.u32 %0, %1, %2;" : "=r"(r) : "r"(addr), "r"(rank));
  return r;
}
__device__ __forceinline__ void wg_fence() { asm volatile("wgmma.fence.sync.aligned;" ::: "memory"); }
__device__ __forceinline__ void wg_commit() { asm volatile("wgmma.commit_group.sync.aligned;" ::: "memory"); }
template <int N> __device__ __forceinline__ void wg_wait() { asm volatile("wgmma.wait_group.sync.aligned %0;" ::"n"(N) : "memory"); }
template <int N> __device__ __forceinline__ void fence_regs(float (&d)[N]) {
#pragma unroll
  for (int i = 0; i < N; i++) asm volatile("" : "+f"(d[i])::"memory");
}
constexpr uint32_t DHI_SW128 = (1024 >> 4) | (1u << 30);
constexpr uint32_t DHI_NONE = (256 >> 4);
__device__ __forceinline__ uint64_t mkdesc(uint32_t lo, uint32_t hi) { return ((uint64_t)hi << 32) | lo; }

__device__ __forceinline__ void wgmma_ss_n112(float (&d)[56], uint64_t da, uint64_t db, int scale_d) {
  asm volatile("{\n.reg .pred p;\nsetp.ne.b32 p, %58, 0;\n"
    "wgmma.mma_async.sync.aligned.m64n112k16.f32.bf16.bf16 "
    "{%0, %1, %2, %3, %4, %5, %6, %7, %8, %9, %10, %11, %12, %13, %14, %15, %16, %17, %18, %19, %20, %21, %22, %23, %24, %25, %26, %27, %28, %29, %30, %31, %32, %33, %34, %35, %36, %37, %38, %39, %40, %41, %42, %43, %44, %45, %46, %47, %48, %49, %50, %51, %52, %53, %54, %55}, "
    "%56, %57, p, 1, 1, 0, 1;\n}\n"
    : "+f"(d[0]), "+f"(d[1]), "+f"(d[2]), "+f"(d[3]), "+f"(d[4]), "+f"(d[5]), "+f"(d[6]), "+f"(d[7]), "+f"(d[8]), "+f"(d[9]), "+f"(d[10]), "+f"(d[11]), "+f"(d[12]), "+f"(d[13]), "+f"(d[14]), "+f"(d[15]), "+f"(d[16]), "+f"(d[17]), "+f"(d[18]), "+f"(d[19]), "+f"(d[20]), "+f"(d[21]), "+f"(d[22]), "+f"(d[23]), "+f"(d[24]), "+f"(d[25]), "+f"(d[26]), "+f"(d[27]), "+f"(d[28]), "+f"(d[29]), "+f"(d[30]), "+f"(d[31]), "+f"(d[32]), "+f"(d[33]), "+f"(d[34]), "+f"(d[35]), "+f"(d[36]), "+f"(d[37]), "+f"(d[38]), "+f"(d[39]), "+f"(d[40]), "+f"(d[41]), "+f"(d[42]), "+f"(d[43]), "+f"(d[44]), "+f"(d[45]), "+f"(d[46]), "+f"(d[47]), "+f"(d[48]), "+f"(d[49]), "+f"(d[50]), "+f"(d[51]), "+f"(d[52]), "+f"(d[53]), "+f"(d[54]), "+f"(d[55])
    : "l"(da), "l"(db), "r"(scale_d));
}
__device__ __forceinline__ void wgmma_ss_n64(float (&d)[32], uint64_t da, uint64_t db, int scale_d) {
  asm volatile("{\n.reg .pred p;\nsetp.ne.b32 p, %34, 0;\n"
    "wgmma.mma_async.sync.aligned.m64n64k16.f32.bf16.bf16 "
    "{%0, %1, %2, %3, %4, %5, %6, %7, %8, %9, %10, %11, %12, %13, %14, %15, %16, %17, %18, %19, %20, %21, %22, %23, %24, %25, %26, %27, %28, %29, %30, %31}, "
    "%32, %33, p, 1, 1, 0, 1;\n}\n"
    : "+f"(d[0]), "+f"(d[1]), "+f"(d[2]), "+f"(d[3]), "+f"(d[4]), "+f"(d[5]), "+f"(d[6]), "+f"(d[7]), "+f"(d[8]), "+f"(d[9]), "+f"(d[10]), "+f"(d[11]), "+f"(d[12]), "+f"(d[13]), "+f"(d[14]), "+f"(d[15]), "+f"(d[16]), "+f"(d[17]), "+f"(d[18]), "+f"(d[19]), "+f"(d[20]), "+f"(d[21]), "+f"(d[22]), "+f"(d[23]), "+f"(d[24]), "+f"(d[25]), "+f"(d[26]), "+f"(d[27]), "+f"(d[28]), "+f"(d[29]), "+f"(d[30]), "+f"(d[31])
    : "l"(da), "l"(db), "r"(scale_d));
}
__device__ __forceinline__ void wgmma_rs2_n128(float (&d0)[32], float (&d1)[32], const uint32_t (&a)[4], uint64_t db, int scale_d) {
  asm volatile("{\n.reg .pred p;\nsetp.ne.b32 p, %69, 0;\n"
    "wgmma.mma_async.sync.aligned.m64n128k16.f32.bf16.bf16 "
    "{%0, %1, %2, %3, %4, %5, %6, %7, %8, %9, %10, %11, %12, %13, %14, %15, %16, %17, %18, %19, %20, %21, %22, %23, %24, %25, %26, %27, %28, %29, %30, %31, %32, %33, %34, %35, %36, %37, %38, %39, %40, %41, %42, %43, %44, %45, %46, %47, %48, %49, %50, %51, %52, %53, %54, %55, %56, %57, %58, %59, %60, %61, %62, %63}, "
    "{%64, %65, %66, %67}, %68, p, 1, 1, 1;\n}\n"
    : "+f"(d0[0]), "+f"(d0[1]), "+f"(d0[2]), "+f"(d0[3]), "+f"(d0[4]), "+f"(d0[5]), "+f"(d0[6]), "+f"(d0[7]), "+f"(d0[8]), "+f"(d0[9]), "+f"(d0[10]), "+f"(d0[11]), "+f"(d0[12]), "+f"(d0[13]), "+f"(d0[14]), "+f"(d0[15]), "+f"(d0[16]), "+f"(d0[17]), "+f"(d0[18]), "+f"(d0[19]), "+f"(d0[20]), "+f"(d0[21]), "+f"(d0[22]), "+f"(d0[23]), "+f"(d0[24]), "+f"(d0[25]), "+f"(d0[26]), "+f"(d0[27]), "+f"(d0[28]), "+f"(d0[29]), "+f"(d0[30]), "+f"(d0[31]), "+f"(d1[0]), "+f"(d1[1]), "+f"(d1[2]), "+f"(d1[3]), "+f"(d1[4]), "+f"(d1[5]), "+f"(d1[6]), "+f"(d1[7]), "+f"(d1[8]), "+f"(d1[9]), "+f"(d1[10]), "+f"(d1[11]), "+f"(d1[12]), "+f"(d1[13]), "+f"(d1[14]), "+f"(d1[15]), "+f"(d1[16]), "+f"(d1[17]), "+f"(d1[18]), "+f"(d1[19]), "+f"(d1[20]), "+f"(d1[21]), "+f"(d1[22]), "+f"(d1[23]), "+f"(d1[24]), "+f"(d1[25]), "+f"(d1[26]), "+f"(d1[27]), "+f"(d1[28]), "+f"(d1[29]), "+f"(d1[30]), "+f"(d1[31])
    : "r"(a[0]), "r"(a[1]), "r"(a[2]), "r"(a[3]), "l"(db), "r"(scale_d));
}
__device__ __forceinline__ void wgmma_ss2_n128(float (&d0)[32], float (&d1)[32], uint64_t da, uint64_t db, int scale_d) {
  asm volatile("{\n.reg .pred p;\nsetp.ne.b32 p, %66, 0;\n"
    "wgmma.mma_async.sync.aligned.m64n128k16.f32.bf16.bf16 "
    "{%0, %1, %2, %3, %4, %5, %6, %7, %8, %9, %10, %11, %12, %13, %14, %15, %16, %17, %18, %19, %20, %21, %22, %23, %24, %25, %26, %27, %28, %29, %30, %31, %32, %33, %34, %35, %36, %37, %38, %39, %40, %41, %42, %43, %44, %45, %46, %47, %48, %49, %50, %51, %52, %53, %54, %55, %56, %57, %58, %59, %60, %61, %62, %63}, "
    "%64, %65, p, 1, 1, 0, 1;\n}\n"
    : "+f"(d0[0]), "+f"(d0[1]), "+f"(d0[2]), "+f"(d0[3]), "+f"(d0[4]), "+f"(d0[5]), "+f"(d0[6]), "+f"(d0[7]), "+f"(d0[8]), "+f"(d0[9]), "+f"(d0[10]), "+f"(d0[11]), "+f"(d0[12]), "+f"(d0[13]), "+f"(d0[14]), "+f"(d0[15]), "+f"(d0[16]), "+f"(d0[17]), "+f"(d0[18]), "+f"(d0[19]), "+f"(d0[20]), "+f"(d0[21]), "+f"(d0[22]), "+f"(d0[23]), "+f"(d0[24]), "+f"(d0[25]), "+f"(d0[26]), "+f"(d0[27]), "+f"(d0[28]), "+f"(d0[29]), "+f"(d0[30]), "+f"(d0[31]), "+f"(d1[0]), "+f"(d1[1]), "+f"(d1[2]), "+f"(d1[3]), "+f"(d1[4]), "+f"(d1[5]), "+f"(d1[6]), "+f"(d1[7]), "+f"(d1[8]), "+f"(d1[9]), "+f"(d1[10]), "+f"(d1[11]), "+f"(d1[12]), "+f"(d1[13]), "+f"(d1[14]), "+f"(d1[15]), "+f"(d1[16]), "+f"(d1[17]), "+f"(d1[18]), "+f"(d1[19]), "+f"(d1[20]), "+f"(d1[21]), "+f"(d1[22]), "+f"(d1[23]), "+f"(d1[24]), "+f"(d1[25]), "+f"(d1[26]), "+f"(d1[27]), "+f"(d1[28]), "+f"(d1[29]), "+f"(d1[30]), "+f"(d1[31])
    : "l"(da), "l"(db), "r"(scale_d));
}

__device__ __forceinline__ float gelu2(float v) {
  const float c0 = 0.7978845608028654f, c1 = 0.7978845608028654f * 0.044715f;
  float u = v * fmaf(c1, v * v, c0);
  float t;
  asm("tanh.approx.f32 %0, %1;" : "=f"(t) : "f"(u));
  return fmaf(v, t, v);
}
__device__ __forceinline__ uint32_t pack_bf16(float lo, float hi) {
  uint32_t r;
  asm("cvt.rn.bf16x2.f32 %0, %1, %2;" : "=r"(r) : "f"(hi), "f"(lo));
  return r;
}
__device__ __forceinline__ float bf_lo(uint32_t v) { return __uint_as_float(v << 16); }
__device__ __forceinline__ float bf_hi(uint32_t v) { return __uint_as_float(v & 0xffff0000u); }
__device__ __forceinline__ void st_frag(uint8_t* p, const uint32_t (&f)[4], uint32_t m0, uint32_t b0, uint32_t m1, uint32_t b1) {
  asm volatile("st.relaxed.gpu.global.v2.u32 [%0], {%1, %2};" ::"l"(p), "r"((f[0] & m0) | b0), "r"(f[2]) : "memory");
  asm volatile("st.relaxed.gpu.global.v2.u32 [%0], {%1, %2};" ::"l"(p + 256), "r"((f[1] & m1) | b1), "r"(f[3]) : "memory");
}
__device__ __forceinline__ uint32_t mbar_try(uint32_t bar, uint32_t parity) {
  uint32_t done;
  asm volatile("{\n.reg .pred p;\nmbarrier.try_wait.parity.shared::cta.b64 p, [%1], %2;\nselp.u32 %0, 1, 0, p;\n}"
               : "=r"(done) : "r"(bar), "r"(parity) : "memory");
  return done;
}
__device__ __forceinline__ void tma5d(uint32_t dst, const CUtensorMap* m, int col, int row, int q, uint32_t bar) {
  asm volatile("cp.async.bulk.tensor.5d.shared::cluster.global.mbarrier::complete_tx::bytes [%0], [%1, {%3, %4, %6, %6, %5}], [%2];"
               ::"r"(dst), "l"(m), "r"(bar), "r"(col), "r"(row), "r"(q), "r"(0) : "memory");
}

template <int N>
__device__ __forceinline__ void gelu_step(const float (&acc)[N], int s, uint32_t (&frag)[4]) {
  const int j = 2 * s;
  frag[0] = pack_bf16(gelu2(acc[4 * j + 0]), gelu2(acc[4 * j + 1]));
  frag[1] = pack_bf16(gelu2(acc[4 * j + 2]), gelu2(acc[4 * j + 3]));
  frag[2] = pack_bf16(gelu2(acc[4 * j + 4]), gelu2(acc[4 * j + 5]));
  frag[3] = pack_bf16(gelu2(acc[4 * j + 6]), gelu2(acc[4 * j + 7]));
}
__device__ __forceinline__ void bulk_load(uint32_t dst, const void* src, uint32_t bytes, uint32_t bar) {
  asm volatile("cp.async.bulk.shared::cluster.global.mbarrier::complete_tx::bytes [%0], [%1], %2, [%3];"
               ::"r"(dst), "l"(src), "r"(bytes), "r"(bar) : "memory");
}

#define STORE_SCHED_1B(kb) do { \
    if ((kb) == 0) st_frag(gh + 0 * 4096, hA[0], tag); \
    if ((kb) == 2) st_frag(gh + 1 * 4096, hA[1], tag); \
    if ((kb) == 3) st_frag(gh + 2 * 4096, hA[2], tag); \
    if ((kb) == 4) st_frag(gh + 3 * 4096, hA[3], tag); \
    if ((kb) == 6) st_frag(gh + 4 * 4096, hA[4], tag); \
    if ((kb) == 7) st_frag(gh + 5 * 4096, hA[5], tag); } while (0)
#define HPROFCNT()
struct Params {
  const __nv_bfloat16* b1;
  const __nv_bfloat16* b2;
  __nv_bfloat16* out;
  uint8_t* h;
  uint32_t* epoch;
  const uint8_t* x;
  const uint8_t* w1;
  const uint8_t* w2;
};

template <int MODE>
__global__ void __launch_bounds__(NTHREADS, 1)
mlp_fused_kernel(const Params prm, const __grid_constant__ CUtensorMap mapX, const __grid_constant__ CUtensorMap mapW1A,
                 const __grid_constant__ CUtensorMap mapW1B, const __grid_constant__ CUtensorMap mapW2A,
                 const __grid_constant__ CUtensorMap mapW2B, const __grid_constant__ CUtensorMap mapW2P1,
                 const __grid_constant__ CUtensorMap mapW2P2, const __grid_constant__ CUtensorMap mapW2P3,
                 const __grid_constant__ CUtensorMap mapW1C) {
  extern __shared__ __align__(1024) uint8_t smem[];
  const uint32_t sbase = smem_u32(smem);
  const uint32_t bars = sbase + SM_BAR;
  const int warp = __shfl_sync(0xffffffff, threadIdx.x >> 5, 0);
  const int lane = threadIdx.x & 31;
  const int c = blockIdx.x >> 1;
  const int r = blockIdx.x & 1;
  int m, p;
  if (MODE == 1) {
    const int d = c - 36;
    const int p7 = (d * 37) >> 8;
    m = c < 4 ? 15 : (c < 36 ? ((c - 4) & 7) : 8 + d - p7 * 7);
    p = c < 4 ? c : (c < 36 ? ((c - 4) >> 3) : p7);
  } else {
    m = (c & 7) + ((c >> 5) << 3); p = (c >> 3) & 3;
  }
  const int f = 2 * p + r;
  const int c0 = f * CH;
#define FULL(s) (bars + 8 * (B_FULL + (s)))
#define EMPTY(s) (bars + 8 * (B_EMPTY + (s)))
#define SLOTA(s) (sbase + (s) * SLOT)
#define ACQ(s, u, bytes) do { if ((u) > 0) mbar_wait(EMPTY(s), ((u) - 1) & 1); mbar_expect_tx(FULL(s), bytes); } while (0)
#define LDX(kb) do { ACQ(kb, 0, 16384); tma2d(SLOTA(kb), &mapX, (kb) * 64, m * 128, FULL(kb)); } while (0)
#define LDA(kb, s, u) do { ACQ(s, u, 8192 + 6144); tma2d(SLOTA(s), &mapW1A, c0, (kb) * 64, FULL(s)); \
                           tma2d(SLOTA(s) + 8192, &mapW1C, c0 + 64, (kb) * 64, FULL(s)); } while (0)

#define FULL2(j) (bars + 8 * ((j) >= 11 ? B_FULL3 + (j) - 11 : B_FULL2 + (j) % 6))
#define PAR2(j) ((j) >= 8 && (j) <= 10)
  if (__builtin_expect(warp >= 8, 1)) {
    asm volatile("setmaxnreg.dec.sync.aligned.u32 56;");
    if (warp == 8) {
    if (elect_one()) {
#pragma unroll
      for (int i = 0; i < NSLOT; i++) mbar_init(FULL(i), 1);
      mbar_init(bars + 8 * (B_RED + 0), 1); mbar_init(bars + 8 * (B_RED + 1), 1); mbar_init(bars + 8 * B_PEER, 1);
      asm volatile("fence.mbarrier_init.release.cluster;" ::: "memory");
      PROF1(54);
    }
    __syncwarp();
    asm volatile("bar.arrive 1, 288;" ::: "memory");
    if (elect_one()) {
      mbar_arrive(FULL(0)); mbar_arrive(FULL(8));
      LDX(1); LDA(1, 9, 0);
      PROF1(55);
      LDX(2); LDA(2, 10, 0); LDX(3); LDA(3, 11, 0); LDX(4); LDA(4, 12, 0); LDX(5); LDA(5, 13, 0); LDX(6); LDX(7);
      PROF1(40);
      asm volatile("prefetch.tensormap [%0];" ::"l"(&mapW1B) : "memory");
      asm volatile("prefetch.tensormap [%0];" ::"l"(&mapW2A) : "memory");
      asm volatile("prefetch.tensormap [%0];" ::"l"(&mapW2B) : "memory");
      asm volatile("prefetch.tensormap [%0];" ::"l"(&mapW2P1) : "memory");
      asm volatile("prefetch.tensormap [%0];" ::"l"(&mapW2P2) : "memory");
      asm volatile("prefetch.tensormap [%0];" ::"l"(&mapW2P3) : "memory");
    }
    __syncwarp();
        __syncwarp();
      asm volatile("barrier.cluster.arrive.relaxed.aligned;" ::: "memory");
      asm volatile("bar.sync 2, 384;" ::: "memory");
      if (elect_one()) {
        LDA(6, 8, 1); LDA(7, 9, 1);
#pragma unroll
        for (int i = 0; i < 4; i++) { ACQ(10 + i, 1, 16384); tma2d(SLOTA(10 + i), &mapW1B, c0 + 112, i * 128, FULL(10 + i)); }
        PROF1(41);
        asm volatile("cp.async.bulk.prefetch.L2.global [%0], %1;" ::"l"(prm.w2 + (size_t)blockIdx.x * 11008), "r"(11008) : "memory");
        const int nk = 128 * p + 64 * (1 - r), ns = 128 * p + 64 * r;
#define OWNP(ws, i, step, bar) do { tma2d(SLOTA(ws) + (i) * 2048, &mapW2B, nk, c0 + 16 * (step), bar); \
                                    tma2d(SLOTA(ws) + 8192 + (i) * 2048, &mapW2B, ns, c0 + 16 * (step), bar); } while (0)
        const CUtensorMap* mlo = p == 1 ? &mapW2P1 : (p == 2 ? &mapW2P2 : &mapW2P3);
        const CUtensorMap* mhi = p == 0 ? &mapW2P3 : (p == 1 ? &mapW2P2 : &mapW2P1);
        const CUtensorMap* mhs = p == 0 ? &mapW2P2 : &mapW2P1;
#define REMW(ws, s, bar) do { const uint32_t d0 = SLOTA(ws) + 2048; const int row = 176 * r + 16 * (s); \
          if (p > 0) { tma5d(d0, mlo, nk, row, 0, bar); tma5d(d0 + 8192, mlo, ns, row, 0, bar); } \
          if (p < 3) { \
            if (r == 1 && (s) >= 9) { \
              if (p < 2) { tma5d(d0 + p * 2048, mhs, nk, row, p + 1, bar); tma5d(d0 + 8192 + p * 2048, mhs, ns, row, p + 1, bar); } \
              tma5d(d0 + 4096, &mapW2P1, nk, 0, 4, bar); tma5d(d0 + 8192 + 4096, &mapW2P1, ns, 0, 4, bar); \
            } else { tma5d(d0 + p * 2048, mhi, nk, row, p + 1, bar); tma5d(d0 + 8192 + p * 2048, mhi, ns, row, p + 1, bar); } } } while (0)
#define LDW(j) do { const int ws = 8 + (j) % 6; \
        mbar_wait(EMPTY(ws), (1 + (j) / 6) & 1); mbar_expect_tx(FULL2(j), ((j) <= 5 ? 4096 : 0) + 12288); \
        REMW(ws, (j) - 2, FULL2(j)); \
        if ((j) <= 5) OWNP(ws, 0, (j) + 5, FULL2(j)); PROF1(88 + (j) - 1); if ((j) >= 3) STAMPN(54 + (j) - 3); } while (0)
        const uint8_t* hsrc = prm.h + (size_t)((m * 2 + r) * 11) * 16384;
#define LDH(s) do { const uint32_t hb = bars + 8 * (B_HF + (s) % 8); mbar_expect_tx(hb, 12288); \
          if (p > 0) bulk_load(SLOTA((s) % 8), hsrc + (s) * 16384, p * 4096, hb); \
          if (p < 3) bulk_load(SLOTA((s) % 8) + p * 4096, hsrc + (s) * 16384 + (p + 1) * 4096, (3 - p) * 4096, hb); \
          PROF1(76 + (s)); STAMPH(43 + (s)); } while (0)
        ACQ(8, 2, 16384);
        tma2d(SLOTA(8), &mapW2A, nk, c0, FULL(8)); tma2d(SLOTA(8) + 8192, &mapW2A, ns, c0, FULL(8));
        ACQ(9, 2, 12288);
        OWNP(9, 0, 4, FULL(9)); OWNP(9, 1, 5, FULL(9)); OWNP(9, 2, 6, FULL(9));
        LDW(2);
        LDW(3); PROF1(48); LDH(0); LDH(1);
        LDW(4); LDH(2); LDH(3);
        LDW(5); LDH(4);
        LDW(6); PROF1(49); LDH(5);
        LDW(7); LDH(6); LDH(7);
        LDW(8); LDH(8);
        LDW(9); PROF1(50); LDH(9);
#define LDWP(j, dst, lbo, jq) do { const int qq = (jq) + ((jq) >= p ? 1 : 0); const bool z = (r == 1 && qq == 3); \
          tma5d(dst, &mapW2P1, nk, z ? 0 : 176 * r + 16 * ((j) - 2), z ? 4 : qq, FULL2(j)); \
          tma5d((dst) + (lbo), &mapW2P1, ns, z ? 0 : 176 * r + 16 * ((j) - 2), z ? 4 : qq, FULL2(j)); } while (0)
        mbar_expect_tx(FULL2(11), 12288);
        LDWP(11, SLOTA(6) + 12288, 2048, 0); LDWP(11, SLOTA(7) + 12288, 2048, 1); LDWP(11, SLOTA(0) + 12288, 2048, 2);
        LDW(10);
        mbar_expect_tx(FULL2(12), 12288);
        LDWP(12, SLOTA(10), 8192, 0); LDWP(12, SLOTA(11), 8192, 1); LDWP(12, SLOTA(12), 8192, 2);
        STAMPN(63);
        LDH(10);
        mbar_wait(EMPTY(13), 0);
        mbar_wait(EMPTY(8), 1);
        PROF1(42);
        mbar_expect_tx(bars + 8 * (B_RED + 0), 8192);
        mbar_expect_tx(bars + 8 * (B_RED + 1), 8192);
      }
      __syncwarp();
      asm volatile("barrier.cluster.wait.aligned;" ::: "memory");
      if (elect_one())
        asm volatile("mbarrier.arrive.shared::cluster.b64 _, [%0];" ::"r"(mapa(bars + 8 * B_PEER, r ^ 1)) : "memory");
    } else {
      const int q = warp - 9;
      const uint32_t tag = (prm.epoch[blockIdx.x * 32] + 1) & 1;
      asm volatile("bar.sync 2, 384;" ::: "memory");
      asm volatile("barrier.cluster.arrive.relaxed.aligned;" ::: "memory");
      const uint8_t* src = prm.h + (size_t)((m * 2 + r) * 11) * 16384;
      const uint32_t chk = sbase + lane * 32 + ((lane >> 2) & 3) * 8;
      const uint32_t hr = bars + 8 * (B_HR + q);
      uint32_t rpar = 0;
#pragma unroll 1
      for (int s = q; s < 11; s += 3) {
        const uint32_t slot = (s & 7) * SLOT;
        mbar_wait(bars + 8 * (B_HF + (s & 7)), s >> 3);
        uint32_t spins = 0;
        for (;;) {
          uint32_t all1 = ~0u, any1 = 0;
#pragma unroll
          for (int i = 0; i < 12; i++) {
            uint32_t v;
            asm volatile("ld.shared.u32 %0, [%1];" : "=r"(v) : "r"(chk + slot + i * 1024) : "memory");
            all1 &= v; any1 |= v;
          }
          const uint32_t good = (tag ? all1 : ~any1) & 1u;
          if (__builtin_expect(__all_sync(0xffffffff, good), 1)) break;
          HPROFCNT();
          if (++spins > (1u << 16)) __trap();
          if (elect_one()) {
            mbar_expect_tx(hr, 12288);
            if (p > 0) bulk_load(sbase + slot, src + s * 16384, p * 4096, hr);
            if (p < 3) bulk_load(sbase + slot + p * 4096, src + s * 16384 + (p + 1) * 4096, (3 - p) * 4096, hr);
          }
          __syncwarp();
          mbar_wait(hr, rpar);
          rpar ^= 1;
        }
        const int j = s + 2;
        const uint32_t fb = bars + 8 * (j >= 11 ? B_FULL3 + j - 11 : B_FULL2 + (j >= 6 ? j - 6 : j));
        if (lane == 0) { mbar_arrive(fb); PROF1(64 + s);
          STAMPN(32 + s);
        }
      }
      asm volatile("barrier.cluster.wait.aligned;" ::: "memory");
    }
  } else {
    const int wg = warp >> 2, wq = warp & 3;
    const int t = lane & 3;
    const uint32_t cp_sw = ((threadIdx.x & 7) ^ ((threadIdx.x >> 3) & 7)) << 4;
    const uint32_t cp_dst = sbase + (threadIdx.x >> 3) * 128 + cp_sw;
    const uint8_t* cp_x = prm.x + (size_t)(m * 128 + (threadIdx.x >> 3)) * 1024 + (threadIdx.x & 7) * 16;
    const uint8_t* cp_w = prm.w1 + (size_t)(threadIdx.x >> 3) * 2752 + c0 * 2 + (threadIdx.x & 7) * 16;
#define CPASYNC(dst, src) asm volatile("cp.async.cg.shared.global [%0], [%1], 16;" ::"r"(dst), "l"(src) : "memory")
#define CPBLOCK(kb) do { _Pragma("unroll") for (int i = 0; i < 4; i++) { \
        CPASYNC(cp_dst + (kb) * SLOT + i * 4096, cp_x + (kb) * 128 + i * 32768); \
        CPASYNC(cp_dst + (8 + (kb)) * SLOT + (i >> 1) * 8192 + (i & 1) * 4096, cp_w + ((kb) * 64 + (i & 1) * 32) * 2752 + (i >> 1) * 128); } \
        asm volatile("cp.async.commit_group;" ::: "memory"); } while (0)
    CPBLOCK(0);
    uint32_t bv[22];
    {
      const uint32_t* b1w = reinterpret_cast<const uint32_t*>(prm.b1 + c0) + t;
#pragma unroll
      for (int j = 0; j < 22; j++) {
        bv[j] = 0;
        if (j < 18 || f < 7)
          asm volatile("ld.global.nc.u32 %0, [%1];" : "=r"(bv[j]) : "l"(b1w + 4 * j));
      }
    }
    const uint32_t epoch = prm.epoch[blockIdx.x * 32];
    PROFX(120);
    if (warp == 0) {
      if (elect_one()) {
#pragma unroll
        for (int b = B_EMPTY + 8; b < B_NUM; b++)
          if (b < B_RED || b >= B_FULL2) mbar_init(bars + 8 * b, b < B_RED ? 8 : ((b < B_HF || b >= B_FULL3) ? 2 : 1));
        asm volatile("fence.mbarrier_init.release.cluster;" ::: "memory");
      }
    }
    __syncwarp();
    PROFX(121);
    asm volatile("bar.arrive 2, 384;" ::: "memory");
    asm volatile("setmaxnreg.inc.sync.aligned.u32 224;");
    PROFX(122);
    asm volatile("bar.sync 1, 288;" ::: "memory");
    asm volatile("barrier.cluster.arrive.relaxed.aligned;" ::: "memory");
    PROFX(123);
    float accA[56], accB[32], accK[32], accS[32];
#pragma unroll
    for (int j = 0; j < 14; j++) { accA[4 * j] = accA[4 * j + 2] = bf_lo(bv[j]); accA[4 * j + 1] = accA[4 * j + 3] = bf_hi(bv[j]); }
#pragma unroll
    for (int j = 0; j < 8; j++) { accB[4 * j] = accB[4 * j + 2] = bf_lo(bv[14 + j]); accB[4 * j + 1] = accB[4 * j + 3] = bf_hi(bv[14 + j]); }
    fence_regs(accA); fence_regs(accB);
    PROF(0);

    constexpr uint32_t dbase = 1024 >> 4;
    if ((sbase & 0x3FFFF) != 1024) __trap();
    const uint32_t dx = __shfl_sync(0xffffffff, dbase + wg * 512 + (1u << 16), 0);
    constexpr uint32_t dw = dbase;
#define REL(s) do { if (lane == 0) mbar_arrive(EMPTY(s)); } while (0)
#define SCHED_FENCE(i) do { if (epoch == 0xFFFFFF00u + (i)) __trap(); } while (0)
#define DESC_X(kb, kk) mkdesc(dx + (kb) * 1024 + (kk) * 2, DHI_SW128)
#define DESC_W(s, off, lbo) mkdesc(dw + (s) * 1024 + ((off) >> 4) + (((lbo) >> 4) << 16), DHI_SW128)

    {
      asm volatile("cp.async.wait_group 0;" ::: "memory");
      asm volatile("fence.proxy.async.shared::cta;" ::: "memory");
      asm volatile("bar.sync 6, 256;" ::: "memory");
      PROF(1); STAMP(1);
      wg_fence();
#pragma unroll
      for (int kk = 0; kk < 4; kk++) wgmma_ss_n112(accA, DESC_X(0, kk), DESC_W(8, kk * 2048, 8192), 1);
      wg_commit();
      int s = 9;
#pragma unroll 1
      for (int kb = 1; kb < 8; kb++) {
        mbar_wait(FULL(kb), 0);
        mbar_wait(FULL(s), kb >= 6);
        wg_fence();
#pragma unroll
        for (int kk = 0; kk < 4; kk++) wgmma_ss_n112(accA, DESC_X(kb, kk), DESC_W(s, kk * 2048, 8192), 1);
        wg_commit();
        wg_wait<1>();
        REL(s == 8 ? 13 : s - 1);
        s = (s == 13) ? 8 : s + 1;
      }
    }
    PROF(2);
    const uint32_t tag = (epoch + 1) & 1;
    uint8_t* gh = prm.h + (size_t)((m * 2 + r) * 11) * 16384 + p * 4096 + wg * 2048 + wq * 512 + (t >> 1) * 128 + (lane >> 2) * 16 + (t & 1) * 8;
    const bool tl = (t == 0 || t == 3);
    const uint32_t m0 = (tl && ((lane >> 2) & 1) == 0) ? ~1u : ~0u, b0 = (m0 != ~0u) ? tag : 0u;
    const uint32_t m1 = (tl && ((lane >> 2) & 1) == 1) ? ~1u : ~0u, b1 = (m1 != ~0u) ? tag : 0u;
    uint32_t hO[11][4];
#define GELU(s) do { if ((s) < 7) gelu_step(accA, (s), hO[s]); else gelu_step(accB, (s) - 7, hO[s]); \
                     st_frag(gh + (s) * 16384, hO[s], m0, b0, m1, b1); } while (0)
    const uint32_t dh = __shfl_sync(0xffffffff, dbase + wg * 128 + (8u << 16), 0);
#define DESC_W2(j, off) mkdesc(dw + (8 + (j) % 6) * 1024 + ((off) >> 4) + ((8192u >> 4) << 16), DHI_SW128)
#define WOFF(j, q) ((j) == 11 ? ((q) == 2 ? 0 : 6 + (q)) * SLOT + 12288 : (j) == 12 ? (10 + (q)) * SLOT : (8 + (j) % 6) * SLOT + ((q) + 1) * 2048)
#define WLBO(j) ((j) == 11 ? 2048u : 8192u)
#define DESC_WR(j, q, cb) mkdesc(dw + ((WOFF(j, q) + (cb) * WLBO(j)) >> 4) + ((WLBO(j) >> 4) << 16), DHI_SW128)
#define DESC_H(s, q) mkdesc(dh + ((s) % 8) * 1024 + (q) * 256, DHI_NONE)
    uint32_t rdy = 0;
#pragma unroll
    for (int i = 0; i < 4; i++) {
      if (!rdy) mbar_wait(FULL(10 + i), 1);
      STAMP(2 + i);
      wg_fence();
#pragma unroll
      for (int kk = 0; kk < 8; kk++)
        wgmma_ss_n64(accB, DESC_X(2 * i + (kk >> 2), kk & 3), DESC_W(10 + i, kk * 2048, 8192), 1);
      wg_commit();
      wg_wait<1>();
      REL(9 + i);
      if (i == 0) fence_regs(accA);
      SCHED_FENCE(i);
      rdy = i < 3 ? mbar_try(FULL(11 + i), 1) : mbar_try(FULL(8), 0);
      if (i == 0) { GELU(0); GELU(1); }
      if (i == 1) { GELU(2); GELU(3); }
      if (i >= 2) GELU(i + 2);
      PROF(11 + i);
    }
    PROF(3);
    uint32_t b2v[8];
#pragma unroll
    for (int j = 0; j < J0; j++) {
      if (!rdy) { if (j < 2) mbar_wait(FULL(8 + j), 0); else mbar_wait(FULL2(j), PAR2(j)); }
      PROFS(100 + j); STAMP(6 + j);
      wg_fence();
      if (j == 0) {
#pragma unroll
        for (int kk = 0; kk < 4; kk++) wgmma_rs2_n128(accS, accK, hO[kk], DESC_W2(0, kk * 2048), kk != 0);
      } else if (j == 1) {
#pragma unroll
        for (int kk = 0; kk < 3; kk++) wgmma_rs2_n128(accS, accK, hO[4 + kk], DESC_W2(1, kk * 2048), 1);
      } else {
        if (j <= 5) wgmma_rs2_n128(accS, accK, hO[j + 5], DESC_W2(j, 0), 1);
#pragma unroll
        for (int q = 0; q < 3; q++) wgmma_ss2_n128(accS, accK, DESC_H(j - 2, q), DESC_WR(j, q, 0), 1);
      }
      wg_commit();
      wg_wait<1>();
      if (j == 0) { REL(13); fence_regs(accB); }
      else if (j <= 7) REL(8 + (j - 1) % 6);
      SCHED_FENCE(4 + j);
      if (j < J0 - 1) rdy = (j == 0) ? mbar_try(FULL(9), 0) : mbar_try(FULL2(j + 1), PAR2(j + 1));
      if (j == J0 - 1) {
        rdy = 1;
#pragma unroll
        for (int jj = J0; jj < JW; jj++) rdy &= mbar_try(FULL2(jj), PAR2(jj));
      }
      if (J0 > 8 && j == J0 - 1) mbar_wait(bars + 8 * B_PEER, 0);
      if (j == 0) { GELU(6); GELU(7); }
      if (j >= 1 && j <= 3) GELU(j + 7);
      if (j == 5) asm volatile("barrier.cluster.wait.aligned;" ::: "memory");
      if (j == 6) {
        const uint32_t* b2w = reinterpret_cast<const uint32_t*>(prm.b2 + 128 * p + 64 * r) + t;
#pragma unroll
        for (int jj = 0; jj < 8; jj++) b2v[jj] = __ldg(b2w + 4 * jj);
      }
      if (j == 1) PROF(4); if (j == 3) PROF(5); if (j == 5) PROF(6);
    }
    PROF(7);
    float accK2[32];
#define BAR_IF(w, ins) asm volatile("{\n.reg .pred p;\nsetp.eq.u32 p, %0, " #w ";\n@p " ins "\n}" ::"r"(wg) : "memory")
    if (!rdy) {
#pragma unroll
      for (int j = J0; j < JW; j++) mbar_wait(FULL2(j), PAR2(j));
    }
    STAMP(6 + J0); STAMP1(24);
    if (J0 == 7) { wg_wait<0>(); REL(8); }
    if (TAIL_ORDER) BAR_IF(1, "bar.sync 3, 256;");
    wg_fence();
#pragma unroll
    for (int j = J0; j < 13; j++) {
      if (j >= JW) { mbar_wait(FULL2(j), PAR2(j)); wg_fence(); }
#pragma unroll
      for (int q = 0; q < 3; q++) wgmma_ss_n64(accS, DESC_H(j - 2, q), DESC_WR(j, q, 0), 1);
    }
    wg_commit();
    if (TAIL_ORDER) { BAR_IF(0, "bar.arrive 3, 256;"); BAR_IF(1, "bar.arrive 4, 256;"); }
    STAMP(7 + J0); STAMP1(25);
    const int tw = threadIdx.x & 127;
    const uint32_t rbuf = SLOTA(4) + wg * 8192 + tw * 16;
    wg_wait<0>();
    fence_regs(accS); fence_regs(accK);
    if (J0 <= 8) mbar_wait(bars + 8 * B_PEER, 0);
    PROF(8); STAMP(19); STAMP1(28);
    {
      const uint32_t rdst = mapa(rbuf, r ^ 1);
      const uint32_t rbar = mapa(bars + 8 * (B_RED + wg), r ^ 1);
#pragma unroll
      for (int q = 0; q < 4; q++)
        asm volatile("st.async.weak.shared::cluster.mbarrier::complete_tx::bytes.v4.b32 [%0], {%1, %2, %3, %4}, [%5];"
                     ::"r"(rdst + q * 2048), "r"(pack_bf16(accS[8 * q + 0], accS[8 * q + 1])), "r"(pack_bf16(accS[8 * q + 2], accS[8 * q + 3])),
                       "r"(pack_bf16(accS[8 * q + 4], accS[8 * q + 5])), "r"(pack_bf16(accS[8 * q + 6], accS[8 * q + 7])), "r"(rbar) : "memory");
    }
#pragma unroll
    for (int i = 0; i < 32; i++) asm volatile("mov.b32 %0, %1;" : "=f"(accK2[i]) : "f"(accK[i]));
    if (TAIL_ORDER) {
      BAR_IF(0, "bar.sync 4, 256;");
      BAR_IF(1, "bar.sync 5, 256;");
    }
    wg_fence();
#pragma unroll
    for (int j = J0; j < 13; j++) {
#pragma unroll
      for (int q = 0; q < 3; q++) wgmma_ss_n64(accK2, DESC_H(j - 2, q), DESC_WR(j, q, 1), 1);
    }
    wg_commit();
    if (TAIL_ORDER) BAR_IF(0, "bar.arrive 5, 256;");
    mbar_wait(EMPTY(13), 0);
    wg_wait<0>();
    fence_regs(accK2);
#pragma unroll
    for (int q = 0; q < 8; q++) {
      const float bl = bf_lo(b2v[q]), bh = bf_hi(b2v[q]);
      accK2[4 * q + 0] = fmaf(accK2[4 * q + 0], 0.5f, bl); accK2[4 * q + 1] = fmaf(accK2[4 * q + 1], 0.5f, bh);
      accK2[4 * q + 2] = fmaf(accK2[4 * q + 2], 0.5f, bl); accK2[4 * q + 3] = fmaf(accK2[4 * q + 3], 0.5f, bh);
    }
    mbar_wait_cluster(bars + 8 * (B_RED + wg), 0);
    PROF(9); STAMP(20); STAMP1(29);
    uint32_t pk[16];
#pragma unroll
    for (int q = 0; q < 4; q++) {
      uint4 v;
      asm volatile("ld.shared.v4.u32 {%0, %1, %2, %3}, [%4];" : "=r"(v.x), "=r"(v.y), "=r"(v.z), "=r"(v.w) : "r"(rbuf + q * 2048) : "memory");
      pk[4 * q + 0] = pack_bf16(fmaf(bf_lo(v.x), 0.5f, accK2[8 * q + 0]), fmaf(bf_hi(v.x), 0.5f, accK2[8 * q + 1]));
      pk[4 * q + 1] = pack_bf16(fmaf(bf_lo(v.y), 0.5f, accK2[8 * q + 2]), fmaf(bf_hi(v.y), 0.5f, accK2[8 * q + 3]));
      pk[4 * q + 2] = pack_bf16(fmaf(bf_lo(v.z), 0.5f, accK2[8 * q + 4]), fmaf(bf_hi(v.z), 0.5f, accK2[8 * q + 5]));
      pk[4 * q + 3] = pack_bf16(fmaf(bf_lo(v.w), 0.5f, accK2[8 * q + 6]), fmaf(bf_hi(v.w), 0.5f, accK2[8 * q + 7]));
    }
    const uint32_t stg = SLOTA(3) + warp * 2048;
    {
      const int mi = lane >> 3, row = (lane & 7) + 8 * (mi & 1);
#pragma unroll
      for (int q = 0; q < 8; q += 2) {
        const int blk = q + (mi >> 1);
        const uint32_t a = stg + row * 128 + ((blk ^ (row & 7)) << 4);
        asm volatile("stmatrix.sync.aligned.m8n8.x4.shared.b16 [%0], {%1, %2, %3, %4};"
                     ::"r"(a), "r"(pk[2 * q]), "r"(pk[2 * q + 1]), "r"(pk[2 * q + 2]), "r"(pk[2 * q + 3]) : "memory");
      }
    }
    __syncwarp();
    {
      __nv_bfloat16* orow = prm.out + (size_t)(m * 128 + wg * 64 + wq * 16) * DM + 128 * p + 64 * r;
#pragma unroll
      for (int i = 0; i < 4; i++) {
        const int row = i * 4 + (lane >> 3), ch = lane & 7;
        uint4 v;
        asm volatile("ld.shared.v4.u32 {%0, %1, %2, %3}, [%4];" : "=r"(v.x), "=r"(v.y), "=r"(v.z), "=r"(v.w)
                     : "r"(stg + row * 128 + ((ch ^ (row & 7)) << 4)) : "memory");
        *reinterpret_cast<uint4*>(orow + row * DM + ch * 8) = v;
      }
    }
    if (threadIdx.x == 0) prm.epoch[blockIdx.x * 32] = epoch + 1;
    PROF(10); STAMP(21); STAMP1(30);
  }
}

typedef CUresult (*EncodeFn)(CUtensorMap*, CUtensorMapDataType, cuuint32_t, void*, const cuuint64_t*, const cuuint64_t*,
                             const cuuint32_t*, const cuuint32_t*, CUtensorMapInterleave, CUtensorMapSwizzle,
                             CUtensorMapL2promotion, CUtensorMapFloatOOBfill);

void make_map(EncodeFn enc, CUtensorMap* map, const void* ptr, uint64_t cols, uint64_t rows, uint32_t box_cols, uint32_t box_rows,
              CUtensorMapL2promotion promo = CU_TENSOR_MAP_L2_PROMOTION_L2_128B) {
  cuuint64_t dims[2] = {cols, rows};
  cuuint64_t strides[1] = {cols * 2};
  cuuint32_t box[2] = {box_cols, box_rows};
  cuuint32_t es[2] = {1, 1};
  enc(map, CU_TENSOR_MAP_DATA_TYPE_BFLOAT16, 2, const_cast<void*>(ptr), dims, strides, box, es, CU_TENSOR_MAP_INTERLEAVE_NONE,
      CU_TENSOR_MAP_SWIZZLE_128B, promo, CU_TENSOR_MAP_FLOAT_OOB_FILL_NONE);
}

void make_map_perm(EncodeFn enc, CUtensorMap* map, const void* ptr, uint32_t nq) {
  cuuint64_t dims[5] = {512, 352, 2, 4, 4};
  cuuint64_t strides[4] = {1024, 8 * 1024, 2 * 1024, 352 * 1024};
  cuuint32_t box[5] = {64, 2, 2, 4, nq};
  cuuint32_t es[5] = {1, 1, 1, 1, 1};
  enc(map, CU_TENSOR_MAP_DATA_TYPE_BFLOAT16, 5, const_cast<void*>(ptr), dims, strides, box, es, CU_TENSOR_MAP_INTERLEAVE_NONE,
      CU_TENSOR_MAP_SWIZZLE_128B, CU_TENSOR_MAP_L2_PROMOTION_L2_128B, CU_TENSOR_MAP_FLOAT_OOB_FILL_NONE);
}

}

extern "C" void kernel_launch(void* const* d_in, const int* in_sizes, int n_in, void* d_out, int out_size) {
  (void)in_sizes; (void)n_in; (void)out_size;
  static EncodeFn enc = nullptr;
  static int mode = 0;
  static uint8_t* scratch = nullptr;
  static uint32_t* counters = nullptr;
  if (!enc) {
    void* fn = nullptr;
    cudaDriverEntryPointQueryResult q;
    cudaGetDriverEntryPoint("cuTensorMapEncodeTiled", &fn, cudaEnableDefault, &q);
    enc = (EncodeFn)fn;
    cudaGetSymbolAddress((void**)&scratch, g_h);
    cudaGetSymbolAddress((void**)&counters, g_epoch);
    cudaFuncSetAttribute(mlp_fused_kernel<0>, cudaFuncAttributeMaxDynamicSharedMemorySize, SMEM_BYTES);
    cudaFuncSetAttribute(mlp_fused_kernel<1>, cudaFuncAttributeMaxDynamicSharedMemorySize, SMEM_BYTES);
    cudaLaunchConfig_t cfg = {};
    cfg.gridDim = dim3(128); cfg.blockDim = dim3(NTHREADS); cfg.dynamicSmemBytes = SMEM_BYTES;
    cudaLaunchAttribute at[1];
    at[0].id = cudaLaunchAttributeClusterDimension;
    at[0].val.clusterDim.x = 8; at[0].val.clusterDim.y = 1; at[0].val.clusterDim.z = 1;
    cfg.attrs = at; cfg.numAttrs = 1;
    int n8 = 0;
    if (cudaOccupancyMaxActiveClusters(&n8, mlp_fused_kernel<1>, &cfg) != cudaSuccess) { n8 = 0; (void)cudaGetLastError(); }
    mode = (n8 == 15) ? 1 : 0;
  }
  CUtensorMap mX, mW1A, mW1B, mW2A, mW2B, mW2P1, mW2P2, mW2P3, mW1C;
  make_map(enc, &mX, d_in[0], DM, TOK, 64, 128, XPROMO);
  make_map(enc, &mW1A, d_in[1], FF, DM, 64, 64, WPROMO);
  make_map(enc, &mW1B, d_in[1], FF, DM, 64, 128);
  make_map(enc, &mW2A, d_in[3], DM, FF, 64, 64);
  make_map(enc, &mW2B, d_in[3], DM, FF, 64, 16);
  make_map_perm(enc, &mW2P1, d_in[3], 1);
  make_map_perm(enc, &mW2P2, d_in[3], 2);
  make_map_perm(enc, &mW2P3, d_in[3], 3);
  make_map(enc, &mW1C, d_in[1], FF, DM, 48, 64, WPROMO);
  Params prm;
  prm.b1 = (const __nv_bfloat16*)d_in[2];
  prm.b2 = (const __nv_bfloat16*)d_in[4];
  prm.out = (__nv_bfloat16*)d_out;
  prm.h = scratch;
  prm.epoch = counters;
  prm.x = (const uint8_t*)d_in[0];
  prm.w1 = (const uint8_t*)d_in[1];
  prm.w2 = (const uint8_t*)d_in[3];
  cudaLaunchConfig_t cfg = {};
  cfg.gridDim = dim3(128); cfg.blockDim = dim3(NTHREADS); cfg.dynamicSmemBytes = SMEM_BYTES;
  cfg.stream = cudaStreamPerThread;
  cudaLaunchAttribute at[1];
  at[0].id = cudaLaunchAttributeClusterDimension;
  at[0].val.clusterDim.x = 2; at[0].val.clusterDim.y = 1; at[0].val.clusterDim.z = 1;
  cfg.attrs = at; cfg.numAttrs = 1;
  if (mode == 1) cudaLaunchKernelEx(&cfg, mlp_fused_kernel<1>, prm, mX, mW1A, mW1B, mW2A, mW2B, mW2P1, mW2P2, mW2P3, mW1C);
  else cudaLaunchKernelEx(&cfg, mlp_fused_kernel<0>, prm, mX, mW1A, mW1B, mW2A, mW2B, mW2P1, mW2P2, mW2P3, mW1C);
}
```
